```python
import torch

def _softmax(x, axis=-1):
    return torch.softmax(x, dim=axis)
def _gelu(x):
    return torch.nn.functional.gelu(x, approximate="tanh")
def _silu(x):
    return torch.nn.functional.silu(x)
def _sigmoid(x):
    return torch.sigmoid(x)
def _layernorm(x, axis=-1, eps=1e-5):
    m = x.mean(dim=axis, keepdim=True)
    v = x.var(dim=axis, keepdim=True, unbiased=False)
    return (x - m) / torch.sqrt(v + eps)
def _scatter_add(tgt, idx, src, axis=0):
    return tgt.clone().index_add_(axis, idx, src)
def _segment_sum(src, seg, n):
    out = torch.zeros((n,) + src.shape[1:], dtype=src.dtype)
    return out.index_add_(0, seg, src)
def _pad(x, pw):
    flat = tuple(v for pair in reversed(pw) for v in pair)
    return torch.nn.functional.pad(x, flat)

kernel_name = 'standalone__sliding_block_cached__decode'

def setup_inputs():

    _w = (lambda a: (lambda t: t.to(torch.bfloat16) if t.is_floating_point() else t)(torch.as_tensor(a)))
    B, Sq, D = 1, 1, 512
    Hq, Hkv, Sk, Dh = 32, 8, 32768, 128
    assert Hq % Hkv == 0, (Hq, Hkv)
    return {
        "x": _w((lambda *s: torch.randn(*s, dtype=torch.bfloat16) * 0.8)(B, Sq, D)),
        "k_cache": _w((lambda *s: torch.randn(*s, dtype=torch.bfloat16) * 0.8)(B, Hkv, Sk, Dh)),
        "v_cache": _w((lambda *s: torch.randn(*s, dtype=torch.bfloat16) * 0.05)(B, Hkv, Sk, Dh)),
        "wq": _w((lambda *s: torch.randn(*s, dtype=torch.bfloat16) * 0.8)(D, Hq * Dh) * (D ** -0.5)),
        "wo": _w((lambda *s: torch.randn(*s, dtype=torch.bfloat16) * 0.05)(Hq * Dh, D) * ((Hq * Dh) ** -0.5)),
    }

def reference(x, k_cache, v_cache, wq, wo):
    B, Sq, D = x.shape
    Hq, Dh = 32, 128
    Hkv, Sk = k_cache.shape[1], k_cache.shape[2]
    W = min(4096, max(256, Sk // 4))
    rep = Hq // Hkv
    q = (lambda x, *d: x.permute(*d))((x @ wq).reshape(B, Sq, Hq, Dh), 0, 2, 1, 3)
    k = (lambda x, n, axis: torch.repeat_interleave(x, n, dim=axis))(k_cache[:, :, Sk - W:, :], rep, axis=1)
    v = (lambda x, n, axis: torch.repeat_interleave(x, n, dim=axis))(v_cache[:, :, Sk - W:, :], rep, axis=1)
    scores = torch.einsum("bhqd,bhkd->bhqk", q, k) * (Dh ** -0.5)
    p = _softmax(scores, axis=-1)
    o = torch.einsum("bhqk,bhkd->bhqd", p, v)
    return (lambda x, *d: x.permute(*d))(o, 0, 2, 1, 3).reshape(B, Sq, Hq * Dh) @ wo
```

```cpp
#include <cuda_runtime.h>
#include <cuda.h>
#include <cuda_bf16.h>
#include <stdint.h>

namespace {

constexpr int SK = 32768, WIN = 4096;
constexpr int NCTA = 64, CLUSTER = 8;
constexpr int NTHREADS = 288;

constexpr int BAR_V = 0;
constexpr int BAR_WO = 8;
constexpr int BAR_K = 16;
constexpr int BAR_WQ = 20;
constexpr int BAR_Q = 21, BAR_ST = 22, BAR_O = 23;
constexpr int BAR_FREE = 24;

constexpr int UNIT = 8192;
constexpr int SM_OB = 24 * UNIT;
constexpr int SM_RED = SM_OB + 8192;
constexpr int SM_Q = SM_RED + 2048;
constexpr int Q_ROW = 272;
constexpr int SM_P = SM_Q + 4 * Q_ROW;
constexpr int P_ROW = 1040;
constexpr int SM_MAX = SM_P + 4 * P_ROW;
constexpr int SM_SUM = SM_MAX + 128;
constexpr int SM_ST = SM_SUM + 128;
constexpr int SM_O = SM_ST + 256;
constexpr int SM_BAR = SM_O + 512;
constexpr int SMEM_BYTES = SM_BAR + 256;

constexpr unsigned SPIN_LIMIT = 1u << 20;
constexpr int ACC_STRIDE = 288;

__device__ __align__(1024) unsigned char g_scratch[128 * ACC_STRIDE];

struct Sched { int first, step, wo_gap, wo_step, pf_bytes, mode; };
struct Maps { CUtensorMap wq, k, v, wo; };

#define TS(i)

__device__ __forceinline__ unsigned clk() { unsigned t; asm volatile("mov.u32 %0, %%clock;" : "=r"(t)); return t; }
__device__ __forceinline__ unsigned now_ns() { unsigned t; asm volatile("mov.u32 %0, %%globaltimer_lo;" : "=r"(t)); return t; }
__device__ __forceinline__ uint32_t smem_u32(const void* p) { return (uint32_t)__cvta_generic_to_shared(p); }
__device__ __forceinline__ bool elect() {
    unsigned p; asm volatile("{\n.reg .pred p;\nelect.sync _|p, 0xffffffff;\nselp.u32 %0, 1, 0, p;\n}" : "=r"(p)); return p;
}
__device__ __forceinline__ void mbar_init(uint32_t bar, uint32_t cnt) {
    asm volatile("mbarrier.init.shared::cta.b64 [%0], %1;" :: "r"(bar), "r"(cnt) : "memory");
}
__device__ __forceinline__ void mbar_expect_tx(uint32_t bar, uint32_t bytes) {
    asm volatile("mbarrier.arrive.expect_tx.shared::cta.b64 _, [%0], %1;" :: "r"(bar), "r"(bytes) : "memory");
}
__device__ __forceinline__ void mbar_arrive(uint32_t bar) {
    asm volatile("mbarrier.arrive.shared::cta.b64 _, [%0];" :: "r"(bar) : "memory");
}
__device__ __forceinline__ bool mbar_try(uint32_t bar) {
    unsigned ok;
    asm volatile("{\n.reg .pred p;\nmbarrier.try_wait.parity.acquire.cluster.shared::cta.b64 p, [%1], 0;\nselp.u32 %0, 1, 0, p;\n}"
                 : "=r"(ok) : "r"(bar) : "memory");
    return ok;
}
__device__ __forceinline__ bool mbar_try_cta(uint32_t bar) {
    unsigned ok;
    asm volatile("{\n.reg .pred p;\nmbarrier.try_wait.parity.shared::cta.b64 p, [%1], 0;\nselp.u32 %0, 1, 0, p;\n}"
                 : "=r"(ok) : "r"(bar) : "memory");
    return ok;
}
__device__ __forceinline__ void mbar_wait(uint32_t bar) {
    if (mbar_try_cta(bar)) return;
    unsigned n = 0;
    while (!mbar_try_cta(bar) && ++n < SPIN_LIMIT) {}
}
__device__ __forceinline__ void mbar_wait_cluster(uint32_t bar) {
    if (mbar_try(bar)) return;
    unsigned n = 0;
    while (!mbar_try(bar) && ++n < SPIN_LIMIT) {}
}
__device__ __forceinline__ void tma_load(uint32_t dst, const CUtensorMap* m, int row, int blk, uint32_t bar) {
    asm volatile("cp.async.bulk.tensor.3d.shared::cluster.global.mbarrier::complete_tx::bytes [%0], [%1, {%2, %3, %4}], [%5];"
                 :: "r"(dst), "l"(m), "r"(0), "r"(row), "r"(blk), "r"(bar) : "memory");
}
__device__ __forceinline__ void prefetch_map(const CUtensorMap* m) {
    asm volatile("prefetch.tensormap [%0];" :: "l"(m) : "memory");
}
__device__ __forceinline__ uint32_t mapa(uint32_t addr, uint32_t rank) {
    uint32_t r; asm("mapa.shared::cluster.u32 %0, %1, %2;" : "=r"(r) : "r"(addr), "r"(rank)); return r;
}
__device__ __forceinline__ void st_async32(uint32_t dst, unsigned v, uint32_t bar) {
    asm volatile("st.async.shared::cluster.mbarrier::complete_tx::bytes.b32 [%0], %1, [%2];" :: "r"(dst), "r"(v), "r"(bar) : "memory");
}
__device__ __forceinline__ void st_async64(uint32_t dst, float a, float b, uint32_t bar) {
    asm volatile("st.async.shared::cluster.mbarrier::complete_tx::bytes.v2.f32 [%0], {%1,%2}, [%3];"
                 :: "r"(dst), "f"(a), "f"(b), "r"(bar) : "memory");
}
__device__ __forceinline__ void st_async128(uint32_t dst, float a, float b, float c, float d, uint32_t bar) {
    asm volatile("st.async.shared::cluster.mbarrier::complete_tx::bytes.v4.f32 [%0], {%1,%2,%3,%4}, [%5];"
                 :: "r"(dst), "f"(a), "f"(b), "f"(c), "f"(d), "r"(bar) : "memory");
}
template <int ID, int N> __device__ __forceinline__ void bar_sync() { asm volatile("bar.sync %0, %1;" :: "n"(ID), "n"(N) : "memory"); }
__device__ __forceinline__ float4 atom_add4(void* p, float a, float b, float c, float d) {
    float4 r;
    asm volatile("atom.relaxed.gpu.global.add.v4.f32 {%0,%1,%2,%3}, [%4], {%5,%6,%7,%8};"
                 : "=f"(r.x), "=f"(r.y), "=f"(r.z), "=f"(r.w) : "l"(p), "f"(a), "f"(b), "f"(c), "f"(d) : "memory");
    return r;
}
__device__ __forceinline__ void red_add2(void* p, float a, float b) {
    asm volatile("red.relaxed.gpu.global.add.v2.f32 [%0], {%1,%2};" :: "l"(p), "f"(a), "f"(b) : "memory");
}
__device__ __forceinline__ void ldsm4(uint32_t (&r)[4], uint32_t addr) {
    asm volatile("ldmatrix.sync.aligned.m8n8.x4.shared.b16 {%0,%1,%2,%3}, [%4];"
                 : "=r"(r[0]), "=r"(r[1]), "=r"(r[2]), "=r"(r[3]) : "r"(addr) : "memory");
}
__device__ __forceinline__ void ldsm4t(uint32_t (&r)[4], uint32_t addr) {
    asm volatile("ldmatrix.sync.aligned.m8n8.x4.trans.shared.b16 {%0,%1,%2,%3}, [%4];"
                 : "=r"(r[0]), "=r"(r[1]), "=r"(r[2]), "=r"(r[3]) : "r"(addr) : "memory");
}
__device__ __forceinline__ void mma16816(float (&d)[4], const uint32_t (&a)[4], uint32_t b0, uint32_t b1) {
    asm volatile("mma.sync.aligned.m16n8k16.row.col.f32.bf16.bf16.f32 {%0,%1,%2,%3}, {%4,%5,%6,%7}, {%8,%9}, {%0,%1,%2,%3};"
                 : "+f"(d[0]), "+f"(d[1]), "+f"(d[2]), "+f"(d[3])
                 : "r"(a[0]), "r"(a[1]), "r"(a[2]), "r"(a[3]), "r"(b0), "r"(b1));
}
__device__ __forceinline__ float bf_lo(unsigned u) { return __uint_as_float(u << 16); }
__device__ __forceinline__ float bf_hi(unsigned u) { return __uint_as_float(u & 0xffff0000u); }
__device__ __forceinline__ unsigned pack_bf16(float lo, float hi) {
    unsigned r; asm("cvt.rn.bf16x2.f32 %0, %1, %2;" : "=r"(r) : "f"(hi), "f"(lo)); return r;
}
__device__ __forceinline__ float ex2(float x) { float y; asm("ex2.approx.ftz.f32 %0, %1;" : "=f"(y) : "f"(x)); return y; }
template <typename T> __device__ __forceinline__ void pin(T*& p) { asm volatile("" : "+l"(p)); }

constexpr float SCL = 0.08838834764831845f * 1.4426950408889634f;

__global__ void __cluster_dims__(CLUSTER, 1, 1) __launch_bounds__(NTHREADS, 1)
decode_fused_kernel(const unsigned char* __restrict__ wq, const Sched sched, const unsigned* __restrict__ x,
                    unsigned short* __restrict__ out, unsigned char* __restrict__ acc, const __grid_constant__ Maps maps) {
    extern __shared__ __align__(1024) unsigned char smem[];
    const unsigned t0 = now_ns();
    const int tid = threadIdx.x, lane = tid & 31;
    const unsigned b = blockIdx.x, g = b >> 3, j = b & 7;
    if (tid == 0)
        asm volatile("cp.async.bulk.prefetch.L2.global [%0], %1;" :: "l"(wq + b * (unsigned)sched.pf_bytes), "r"(sched.pf_bytes) : "memory");
    const int warp = __shfl_sync(0xffffffffu, tid >> 5, 0);
    const uint32_t sb = smem_u32(smem);
    const uint32_t bars = sb + SM_BAR;
    if (warp < 8) {
        if (elect()) {
            mbar_init(bars + 8 * (BAR_V + warp), 1); mbar_expect_tx(bars + 8 * (BAR_V + warp), 2 * UNIT);
            mbar_init(bars + 8 * (BAR_WO + warp), 1); mbar_expect_tx(bars + 8 * (BAR_WO + warp), UNIT);
            if (warp != 4) {
                mbar_init(bars + 8 * (BAR_K + warp), 1);
                mbar_expect_tx(bars + 8 * (BAR_K + warp), warp < 4 ? 4 * UNIT : warp == 5 ? 1024 : warp == 6 ? 256 : 8192);
            }
            if (warp < 3) mbar_init(bars + 8 * (BAR_FREE + warp), 8);
            asm volatile("fence.mbarrier_init.release.cluster;" ::: "memory");
            asm volatile("fence.proxy.async.shared::cta;" ::: "memory");
        }
        __syncwarp();
        asm volatile("barrier.cluster.arrive.relaxed.aligned;" ::: "memory");
        const int r = lane >> 2, c = lane & 3, mi = lane >> 3, li = lane & 7;
        uint32_t xb[4][2];
        if (sched.mode & 16) {
#pragma unroll
            for (int ks = 0; ks < 4; ks++) xb[ks][0] = xb[ks][1] = 0x3c003c00;
        } else {
            if (sched.mode & 32) {
                if (b != 0) while ((int)(now_ns() - t0) < 1000) __nanosleep(100);
            }
#pragma unroll
        for (int ks = 0; ks < 4; ks++) {
            xb[ks][0] = __ldg(x + warp * 32 + ks * 8 + c);
            xb[ks][1] = __ldg(x + warp * 32 + ks * 8 + c + 4);
        }
        }
        asm volatile("barrier.cluster.wait.aligned;" ::: "memory");
        {
            const uint32_t qa = sb + (16 + warp) * UNIT + ((mi >> 1) * 8 + li) * 128;
            float d[4][4];
            mbar_wait(bars + 8 * BAR_WQ);
#pragma unroll
            for (int t = 0; t < 4; t++) {
#pragma unroll
                for (int i = 0; i < 4; i++) d[t][i] = 0.f;
#pragma unroll
                for (int ks = 0; ks < 4; ks++) {
                    uint32_t a[4];
                    ldsm4t(a, qa + ks * 2048 + (((t * 2 + (mi & 1)) ^ li) * 16));
                    mma16816(d[t], a, xb[ks][0], xb[ks][1]);
                }
            }
            __syncwarp();
            if (lane == 0) mbar_arrive(bars + 8 * BAR_FREE);
            float* rp = reinterpret_cast<float*>(smem + SM_RED) + warp * 64 + c * 16 + r;
            rp[0] = (c & 2) ? ((c & 1) ? d[3][0] : d[2][0]) : ((c & 1) ? d[1][0] : d[0][0]);
            rp[8] = (c & 2) ? ((c & 1) ? d[3][2] : d[2][2]) : ((c & 1) ? d[1][2] : d[0][2]);
        }
        if (warp == 0) TS(0);
        bar_sync<1, 256>();
        {
            float s0 = 0.f, s1 = 0.f;
#pragma unroll
            for (int w = 0; w < 8; w++) {
                const float2 v = *reinterpret_cast<const float2*>(smem + SM_RED + w * 256 + lane * 8);
                s0 += v.x; s1 += v.y;
            }
            st_async32(mapa(sb + SM_Q + (j >> 1) * Q_ROW + (j & 1) * 128 + lane * 4, warp), pack_bf16(s0, s1),
                       mapa(bars + 8 * BAR_Q, warp));
        }
        if (warp == 0) TS(1);
        mbar_wait_cluster(bars + 8 * BAR_Q);
        if (warp == 0) TS(2);
        float sv[4][4];
        {
            uint32_t qb[8][2];
#pragma unroll
            for (int ks = 0; ks < 8; ks++) {
                const unsigned char* qp = smem + SM_Q + (r & 3) * Q_ROW + ks * 32 + c * 4;
                qb[ks][0] = *reinterpret_cast<const uint32_t*>(qp);
                qb[ks][1] = *reinterpret_cast<const uint32_t*>(qp + 16);
            }
            const uint32_t ka = sb + (warp >> 1) * UNIT + ((warp & 1) * 16 + (mi & 1) * 8 + li) * 128;
#pragma unroll
            for (int i = 0; i < 4; i++) {
                mbar_wait(bars + 8 * (BAR_K + i));
                float s2[4];
#pragma unroll
                for (int k = 0; k < 4; k++) sv[i][k] = s2[k] = 0.f;
                uint32_t a[8][4];
#pragma unroll
                for (int ks = 0; ks < 8; ks++) ldsm4(a[ks], ka + i * 4 * UNIT + (ks >> 2) * 4096 + ((((ks & 3) * 2 + (mi >> 1)) ^ li) * 16));
#pragma unroll
                for (int ks = 0; ks < 8; ks += 2) {
                    mma16816(sv[i], a[ks], qb[ks][0], qb[ks][1]);
                    mma16816(s2, a[ks + 1], qb[ks + 1][0], qb[ks + 1][1]);
                }
#pragma unroll
                for (int k = 0; k < 4; k++) sv[i][k] += s2[k];
                if (i & 1) {
                    __syncwarp();
                    if (lane == 0) mbar_arrive(bars + 8 * (BAR_FREE + 1 + (i >> 1)));
                }
            }
        }
        const int ts = c >> 1, h0 = (c & 1) * 2;
        float s[2][4];
#pragma unroll
        for (int u = 0; u < 2; u++)
#pragma unroll
            for (int k = 0; k < 4; k++) s[u][k] = ts ? sv[2 * u + 1][k] : sv[2 * u][k];
        {
            float m0 = fmaxf(fmaxf(s[0][0], s[0][2]), fmaxf(s[1][0], s[1][2]));
            float m1 = fmaxf(fmaxf(s[0][1], s[0][3]), fmaxf(s[1][1], s[1][3]));
#pragma unroll
            for (int o = 2; o < 32; o <<= 1) {
                m0 = fmaxf(m0, __shfl_xor_sync(0xffffffffu, m0, o));
                m1 = fmaxf(m1, __shfl_xor_sync(0xffffffffu, m1, o));
            }
            if (lane < 2) *reinterpret_cast<float2*>(smem + SM_MAX + warp * 16 + lane * 8) = make_float2(m0, m1);
        }
        if (warp == 7) TS(3);
        bar_sync<1, 256>();
        float m0 = -INFINITY, m1 = -INFINITY;
        {
#pragma unroll
            for (int w = 0; w < 8; w++) {
                const float2 m = *reinterpret_cast<const float2*>(smem + SM_MAX + w * 16 + (c & 1) * 8);
                m0 = fmaxf(m0, m.x); m1 = fmaxf(m1, m.y);
            }
            float l0 = 0.f, l1 = 0.f;
#pragma unroll
            for (int u = 0; u < 2; u++) {
                const unsigned p01 = pack_bf16(ex2((s[u][0] - m0) * SCL), ex2((s[u][1] - m1) * SCL));
                const unsigned p23 = pack_bf16(ex2((s[u][2] - m0) * SCL), ex2((s[u][3] - m1) * SCL));
                unsigned char* pp = smem + SM_P + h0 * P_ROW + (((2 * u + ts) * 8 + warp) * 16 + r) * 2;
                *reinterpret_cast<unsigned short*>(pp) = (unsigned short)p01;
                *reinterpret_cast<unsigned short*>(pp + P_ROW) = (unsigned short)(p01 >> 16);
                *reinterpret_cast<unsigned short*>(pp + 16) = (unsigned short)p23;
                *reinterpret_cast<unsigned short*>(pp + P_ROW + 16) = (unsigned short)(p23 >> 16);
                l0 += bf_lo(p01) + bf_lo(p23); l1 += bf_hi(p01) + bf_hi(p23);
            }
#pragma unroll
            for (int o = 2; o < 32; o <<= 1) {
                l0 += __shfl_xor_sync(0xffffffffu, l0, o);
                l1 += __shfl_xor_sync(0xffffffffu, l1, o);
            }
            if (lane < 2) *reinterpret_cast<float2*>(smem + SM_SUM + warp * 16 + lane * 8) = make_float2(l0, l1);
        }
        bar_sync<1, 256>();
        if (lane < 4) {
            float m = -INFINITY, l = 0.f;
#pragma unroll
            for (int w = 0; w < 8; w++) {
                m = fmaxf(m, *reinterpret_cast<const float*>(smem + SM_MAX + w * 16 + lane * 4));
                l += *reinterpret_cast<const float*>(smem + SM_SUM + w * 16 + lane * 4);
            }
            st_async64(mapa(sb + SM_ST + j * 32 + lane * 8, warp), m, l, mapa(bars + 8 * BAR_ST, warp));
        }
        __syncwarp();
        if (warp == 0) TS(4);
        const unsigned ent = (j & 3) * 64 + warp * 8 + r;
        unsigned char* aptr = acc + (ent >> 1) * ACC_STRIDE + (ent & 1) * 16;
        unsigned short* outp = out + (j & 3) * 128 + warp * 16 + r;
        pin(aptr); pin(outp);
        const uint32_t ta = sb + (warp >> 2) * 4096 + ((mi >> 1) * 8 + li) * 128 + ((((warp & 3) * 2 + (mi & 1)) ^ li) * 16);
        {
            float oa[2][4], w0, w1;
#pragma unroll
            for (int i = 0; i < 4; i++) oa[0][i] = oa[1][i] = 0.f;
            const unsigned char* pp = smem + SM_P + (r & 3) * P_ROW + c * 4;
            const uint32_t dst0 = (c & 1) * 4 + ts * 2;
            const uint32_t oaddr = sb + SM_OB + j * 1024 + (warp * 8 + r) * 16;
            const uint32_t oa0 = mapa(oaddr, dst0), oa1 = mapa(oaddr, dst0 + 1);
            const uint32_t ob0 = mapa(bars + 8 * BAR_O, dst0), ob1 = mapa(bars + 8 * BAR_O, dst0 + 1);
#pragma unroll
            for (int grp = 0; grp < 8; grp++) {
                uint32_t pb[4][2];
#pragma unroll
                for (int u = 0; u < 4; u++) {
                    pb[u][0] = *reinterpret_cast<const uint32_t*>(pp + (grp * 4 + u) * 32);
                    pb[u][1] = *reinterpret_cast<const uint32_t*>(pp + (grp * 4 + u) * 32 + 16);
                }
                if (grp == 4) {
                    mbar_wait_cluster(bars + 8 * BAR_ST);
                    float4 st[8];
                    float M0 = -INFINITY, M1 = -INFINITY;
#pragma unroll
                    for (int k = 0; k < 8; k++) {
                        st[k] = *reinterpret_cast<const float4*>(smem + SM_ST + k * 32 + (c & 1) * 16);
                        M0 = fmaxf(M0, st[k].x); M1 = fmaxf(M1, st[k].z);
                    }
                    float L0 = 0.f, L1 = 0.f;
#pragma unroll
                    for (int k = 0; k < 8; k++) {
                        L0 = fmaf(ex2((st[k].x - M0) * SCL), st[k].y, L0);
                        L1 = fmaf(ex2((st[k].z - M1) * SCL), st[k].w, L1);
                    }
                    w0 = ex2((m0 - M0) * SCL) * __frcp_rn(L0);
                    w1 = ex2((m1 - M1) * SCL) * __frcp_rn(L1);
                    if (warp == 0) TS(5);
                }
                mbar_wait(bars + 8 * (BAR_V + grp));
                if (warp == 0 && grp == 7) TS(8);
                uint32_t a[4][4];
#pragma unroll
                for (int u = 0; u < 4; u++) ldsm4t(a[u], ta + ((grp * 2 + (u >> 1) + 16) % 24) * UNIT + (u & 1) * 2048);
#pragma unroll
                for (int u = 0; u < 4; u++) mma16816(oa[u & 1], a[u], pb[u][0], pb[u][1]);
            }
            const float v0 = (oa[0][0] + oa[1][0]) * w0, v1 = (oa[0][1] + oa[1][1]) * w1;
            const float v2 = (oa[0][2] + oa[1][2]) * w0, v3 = (oa[0][3] + oa[1][3]) * w1;
            st_async128(oa0, v0, v1, v2, v3, ob0);
            st_async128(oa1, v0, v1, v2, v3, ob1);
        }
        if (warp == 0) TS(9);
        {
            mbar_wait_cluster(bars + 8 * BAR_O);
            if (warp == 0) TS(10);
            float v[8];
#pragma unroll
            for (int k = 0; k < 8; k++) v[k] = *reinterpret_cast<const float*>(smem + SM_OB + k * 1024 + tid * 4);
            const float o = ((v[0] + v[1]) + (v[2] + v[3])) + ((v[4] + v[5]) + (v[6] + v[7]));
            *reinterpret_cast<unsigned short*>(smem + SM_O + ((c & 1) * 4 + (warp >> 1)) * 64 + (r >> 1) * 16 + (warp & 1) * 8 + ts * 4 + (r & 1) * 2)
                = (unsigned short)pack_bf16(o, o);
        }
        bar_sync<1, 256>();
        {
            uint4 ob[8];
#pragma unroll
            for (int k = 0; k < 8; k++) ob[k] = *reinterpret_cast<const uint4*>(smem + SM_O + k * 64 + c * 16);
            if (warp == 0) TS(11);
            float d[2][4];
#pragma unroll
            for (int i = 0; i < 4; i++) d[0][i] = d[1][i] = 0.f;
#pragma unroll
            for (int k = 0; k < 8; k++) {
                mbar_wait(bars + 8 * (BAR_WO + k));
                if (warp == 0 && k == 7) TS(14);
                uint32_t a0[4], a1[4];
                ldsm4t(a0, ta + (8 + k) * UNIT);
                ldsm4t(a1, ta + (8 + k) * UNIT + 2048);
                mma16816(d[0], a0, ob[k].x, ob[k].y);
                mma16816(d[1], a1, ob[k].z, ob[k].w);
                if (k == 1 && (sched.mode & 1)) {
                    if (c == 0) red_add2(aptr, d[0][0] + d[1][0], d[0][2] + d[1][2]);
#pragma unroll
                    for (int i = 0; i < 4; i++) d[0][i] = d[1][i] = 0.f;
                    if (warp == 0) TS(12);
                }
            }
            if (c == 0) {
                const float v0 = d[0][0] + d[1][0], v1 = d[0][2] + d[1][2];
                const float4 old = atom_add4(aptr, v0, v1, 1.f, 0.f);
                if (old.z == 15.f) {
                    const unsigned o2 = pack_bf16(old.x + v0, old.y + v1);
                    outp[0] = (unsigned short)o2;
                    outp[8] = (unsigned short)(o2 >> 16);
                    *reinterpret_cast<float4*>(aptr) = make_float4(0.f, 0.f, 0.f, 0.f);
                }
            }
        }
    } else {
        unsigned due = t0 + sched.first;
        if (elect()) {
            prefetch_map(&maps.wq);
            mbar_init(bars + 8 * BAR_WQ, 1); mbar_expect_tx(bars + 8 * BAR_WQ, 8 * UNIT);
            asm volatile("fence.mbarrier_init.release.cluster;" ::: "memory");
            asm volatile("fence.proxy.async.shared::cta;" ::: "memory");
        }
        __syncwarp();
        asm volatile("barrier.cluster.arrive.relaxed.aligned;" ::: "memory");
        TS(35);
        if (elect()) {
#pragma unroll 1
            for (int s = 0; s < 8; s++) {
                while ((int)(now_ns() - due) < 0) {}
                tma_load(sb + (16 + s) * UNIT, &maps.wq, s * 64, b, bars + 8 * BAR_WQ);
                due += sched.step;
                if (s == 1) { prefetch_map(&maps.k); prefetch_map(&maps.v); prefetch_map(&maps.wo); }
            }
        }
        __syncwarp();
        asm volatile("barrier.cluster.wait.aligned;" ::: "memory");
        TS(36);
        if (elect()) {
            const int key0 = g * SK + (SK - WIN) + j * 512;
#pragma unroll 1
            for (int s = 0; s < 16; s++) {
                while ((int)(now_ns() - due) < 0) {}
                tma_load(sb + s * UNIT, &maps.k, key0 + s * 32, 0, bars + 8 * (BAR_K + (s >> 2)));
                due += sched.step;
            }
#pragma unroll
            for (int h = 0; h < 2; h++) {
                mbar_wait(bars + 8 * (BAR_FREE + h));
#pragma unroll 1
                for (int s = 0; s < 8; s++) {
                    while ((int)(now_ns() - due) < 0) {}
                    tma_load(sb + ((h ? 0 : 16) + s) * UNIT, &maps.v, key0 + (h * 8 + s) * 32, 0, bars + 8 * (BAR_V + h * 4 + (s >> 1)));
                    due += sched.step;
                }
            }
            TS(37);
            due += sched.wo_gap;
            mbar_wait(bars + 8 * (BAR_FREE + 2));
#pragma unroll 1
            for (int s = 0; s < 8; s++) {
                while ((int)(now_ns() - due) < 0) {}
                tma_load(sb + (8 + s) * UNIT, &maps.wo, (b >> 2) * 256 + s * 32, (j & 3) * 2, bars + 8 * (BAR_WO + s));
                due += sched.wo_step;
            }
            TS(38);
        }
    }
}

}

typedef CUresult (*EncodeFn)(CUtensorMap*, CUtensorMapDataType, cuuint32_t, void*, const cuuint64_t*, const cuuint64_t*,
                             const cuuint32_t*, const cuuint32_t*, CUtensorMapInterleave, CUtensorMapSwizzle,
                             CUtensorMapL2promotion, CUtensorMapFloatOOBfill);

static void make_map(EncodeFn enc, CUtensorMap* m, void* p, uint64_t rows, uint64_t nblk, uint32_t box_rows, uint32_t box_blks) {
    const cuuint64_t dims[3] = {64, rows, nblk}, strides[2] = {nblk * 128, 128};
    const cuuint32_t box[3] = {64, box_rows, box_blks}, es[3] = {1, 1, 1};
    enc(m, CU_TENSOR_MAP_DATA_TYPE_BFLOAT16, 3, p, dims, strides, box, es, CU_TENSOR_MAP_INTERLEAVE_NONE,
        CU_TENSOR_MAP_SWIZZLE_128B, CU_TENSOR_MAP_L2_PROMOTION_NONE, CU_TENSOR_MAP_FLOAT_OOB_FILL_NONE);
}

extern "C" void kernel_launch(void* const* d_in, const int* in_sizes, int n_in, void* d_out, int out_size) {
    EncodeFn enc = nullptr;
    cudaDriverEntryPointQueryResult qr;
    cudaGetDriverEntryPoint("cuTensorMapEncodeTiled", (void**)&enc, cudaEnableDefault, &qr);
    Maps maps;
    make_map(enc, &maps.wq, d_in[3], 512, 64, 64, 1);
    make_map(enc, &maps.k, d_in[1], 8 * SK, 2, 32, 2);
    make_map(enc, &maps.v, d_in[2], 8 * SK, 2, 32, 2);
    make_map(enc, &maps.wo, d_in[4], 4096, 8, 32, 2);
    void* acc = nullptr;
    cudaGetSymbolAddress(&acc, g_scratch);
    cudaFuncSetAttribute(decode_fused_kernel, cudaFuncAttributeMaxDynamicSharedMemorySize, SMEM_BYTES);
    Sched s;
    s.first = -350; s.step = 170; s.wo_gap = 0; s.wo_step = 160; s.pf_bytes = 16384; s.mode = 33;
    decode_fused_kernel<<<NCTA, NTHREADS, SMEM_BYTES>>>((const unsigned char*)d_in[3], s, (const unsigned*)d_in[0],
                                                        (unsigned short*)d_out, (unsigned char*)acc, maps);
}
```

```cpp
#include <cuda_runtime.h>
#include <cuda.h>
#include <cuda_bf16.h>
#include <stdint.h>

namespace {

constexpr int SK = 32768, WIN = 4096;
constexpr int NCTA = 64, CLUSTER = 8;
#define NCW 2
constexpr int NPAIR = 256 + 32 * NCW;
constexpr int NTHREADS = NPAIR + 32;

constexpr int BAR_V = 0;
constexpr int BAR_WO = 8;
constexpr int BAR_Q = 16, BAR_ST = 17, BAR_O = 18;
constexpr int BAR_FREE = 19;
constexpr int BAR_K = 22;
constexpr int BAR_WQ = 26;

constexpr int UNIT = 8192;
constexpr int SM_OB = 24 * UNIT;
constexpr int SM_RED = SM_OB + 8192;
constexpr int SM_Q = SM_RED + 2048;
constexpr int Q_ROW = 320;
constexpr int SM_P = SM_Q + 4 * Q_ROW;
constexpr int P_ROW = 1088;
constexpr int SM_MAX = SM_P + 4 * P_ROW;
constexpr int SM_SUM = SM_MAX + 128;
constexpr int SM_ST = SM_SUM + 128;
constexpr int SM_O = SM_ST + 256;
constexpr int SM_X = SM_O + 512;
constexpr int SM_BAR = SM_X + 1024;
constexpr int SMEM_BYTES = SM_BAR + 256;

constexpr int NPF = 2;
constexpr unsigned SPIN_LIMIT = 1u << 20;

constexpr int ACC_STRIDE = 256;
__device__ __align__(8192) unsigned char g_scratch[(32 + 4) * ACC_STRIDE];

struct Sched { int first, step, wo_gap, wo_step; };
struct Maps { CUtensorMap wq, v, wo; };

#define TS(i)

__device__ __forceinline__ unsigned now_ns() { unsigned t; asm volatile("mov.u32 %0, %%globaltimer_lo;" : "=r"(t)); return t; }
__device__ __forceinline__ void wait_until(unsigned t) { while ((int)(now_ns() - t) < 0) {} }
__device__ __forceinline__ uint32_t smem_u32(const void* p) { return (uint32_t)__cvta_generic_to_shared(p); }
__device__ __forceinline__ bool elect() {
    unsigned p; asm volatile("{\n.reg .pred p;\nelect.sync _|p, 0xffffffff;\nselp.u32 %0, 1, 0, p;\n}" : "=r"(p)); return p;
}
__device__ __forceinline__ void mbar_init(uint32_t bar, uint32_t cnt) {
    asm volatile("mbarrier.init.shared::cta.b64 [%0], %1;" :: "r"(bar), "r"(cnt) : "memory");
}
__device__ __forceinline__ void mbar_init_tx(uint32_t bar, uint32_t bytes) {
    mbar_init(bar, 1);
    asm volatile("mbarrier.arrive.expect_tx.shared::cta.b64 _, [%0], %1;" :: "r"(bar), "r"(bytes) : "memory");
}
__device__ __forceinline__ void mbar_init_fence() { asm volatile("fence.mbarrier_init.release.cluster;" ::: "memory"); }
__device__ __forceinline__ void mbar_arrive(uint32_t bar) {
    asm volatile("mbarrier.arrive.shared::cta.b64 _, [%0];" :: "r"(bar) : "memory");
}
__device__ __forceinline__ void mbar_wait(uint32_t bar) {
    unsigned ok, n = 0;
    do {
        ++n;
        asm volatile("{\n.reg .pred p;\nmbarrier.try_wait.parity.shared::cta.b64 p, [%1], 0;\nselp.u32 %0, 1, 0, p;\n}"
                     : "=r"(ok) : "r"(bar) : "memory");
    } while (!ok && n < SPIN_LIMIT);
}
__device__ __forceinline__ void mbar_wait_remote(uint32_t bar) {
    unsigned ok, n = 0;
    do {
        ++n;
        asm volatile("{\n.reg .pred p;\nmbarrier.try_wait.parity.relaxed.cluster.shared::cta.b64 p, [%1], 0;\nselp.u32 %0, 1, 0, p;\n}"
                     : "=r"(ok) : "r"(bar) : "memory");
    } while (!ok && n < SPIN_LIMIT);
    asm volatile("fence.acquire.sync_restrict::shared::cluster.cluster;" ::: "memory");
}
__device__ __forceinline__ void bulk_load(uint32_t dst, const void* src, uint32_t bytes, uint32_t bar) {
    asm volatile("cp.async.bulk.shared::cluster.global.mbarrier::complete_tx::bytes [%0], [%1], %2, [%3];"
                 :: "r"(dst), "l"(src), "r"(bytes), "r"(bar) : "memory");
}
__device__ __forceinline__ void tma_load(uint32_t dst, const CUtensorMap* m, int row, int blk, uint32_t bar) {
    asm volatile("cp.async.bulk.tensor.3d.shared::cluster.global.mbarrier::complete_tx::bytes [%0], [%1, {%2, %3, %4}], [%5];"
                 :: "r"(dst), "l"(m), "r"(0), "r"(row), "r"(blk), "r"(bar) : "memory");
}
__device__ __forceinline__ void prefetch_map(const CUtensorMap* m) {
    asm volatile("prefetch.tensormap [%0];" :: "l"(m) : "memory");
}
__device__ __forceinline__ uint32_t mapa(uint32_t addr, uint32_t rank) {
    uint32_t r; asm("mapa.shared::cluster.u32 %0, %1, %2;" : "=r"(r) : "r"(addr), "r"(rank)); return r;
}
__device__ __forceinline__ void st_async32(uint32_t dst, unsigned v, uint32_t bar) {
    asm volatile("st.async.shared::cluster.mbarrier::complete_tx::bytes.b32 [%0], %1, [%2];" :: "r"(dst), "r"(v), "r"(bar) : "memory");
}
__device__ __forceinline__ void st_async64(uint32_t dst, float a, float b, uint32_t bar) {
    asm volatile("st.async.shared::cluster.mbarrier::complete_tx::bytes.v2.f32 [%0], {%1,%2}, [%3];"
                 :: "r"(dst), "f"(a), "f"(b), "r"(bar) : "memory");
}
__device__ __forceinline__ void st_async128(uint32_t dst, float a, float b, float c, float d, uint32_t bar) {
    asm volatile("st.async.shared::cluster.mbarrier::complete_tx::bytes.v4.f32 [%0], {%1,%2,%3,%4}, [%5];"
                 :: "r"(dst), "f"(a), "f"(b), "f"(c), "f"(d), "r"(bar) : "memory");
}
template <int ID, int N> __device__ __forceinline__ void bar_sync() { asm volatile("bar.sync %0, %1;" :: "n"(ID), "n"(N) : "memory"); }
template <int ID, int N> __device__ __forceinline__ void bar_arrive() { asm volatile("bar.arrive %0, %1;" :: "n"(ID), "n"(N) : "memory"); }
__device__ __forceinline__ void cluster_sync_relaxed() {
    asm volatile("barrier.cluster.arrive.relaxed.aligned;\nbarrier.cluster.wait.aligned;" ::: "memory");
}
__device__ __forceinline__ float2 atom_add2(void* p, float a, float b) {
    float2 r;
    asm volatile("atom.relaxed.gpu.global.add.v2.f32 {%0,%1}, [%2], {%3,%4};"
                 : "=f"(r.x), "=f"(r.y) : "l"(p), "f"(a), "f"(b) : "memory");
    return r;
}
__device__ __forceinline__ void ldsm4t(uint32_t (&r)[4], uint32_t addr) {
    asm volatile("ldmatrix.sync.aligned.m8n8.x4.trans.shared.b16 {%0,%1,%2,%3}, [%4];"
                 : "=r"(r[0]), "=r"(r[1]), "=r"(r[2]), "=r"(r[3]) : "r"(addr) : "memory");
}
__device__ __forceinline__ void mma16816(float (&d)[4], uint32_t a0, uint32_t a1, uint32_t a2, uint32_t a3, uint32_t b0, uint32_t b1) {
    asm volatile("mma.sync.aligned.m16n8k16.row.col.f32.bf16.bf16.f32 {%0,%1,%2,%3}, {%4,%5,%6,%7}, {%8,%9}, {%0,%1,%2,%3};"
                 : "+f"(d[0]), "+f"(d[1]), "+f"(d[2]), "+f"(d[3])
                 : "r"(a0), "r"(a1), "r"(a2), "r"(a3), "r"(b0), "r"(b1));
}
__device__ __forceinline__ void mma16816(float (&d)[4], const uint32_t (&a)[4], uint32_t b0, uint32_t b1) {
    mma16816(d, a[0], a[1], a[2], a[3], b0, b1);
}
__device__ __forceinline__ float bf_lo(unsigned u) { return __uint_as_float(u << 16); }
__device__ __forceinline__ float bf_hi(unsigned u) { return __uint_as_float(u & 0xffff0000u); }
__device__ __forceinline__ unsigned pack_bf16(float lo, float hi) {
    unsigned r; asm("cvt.rn.bf16x2.f32 %0, %1, %2;" : "=r"(r) : "f"(hi), "f"(lo)); return r;
}
__device__ __forceinline__ float ex2(float x) { float y; asm("ex2.approx.ftz.f32 %0, %1;" : "=f"(y) : "f"(x)); return y; }
template <typename T> __device__ __forceinline__ void pin(T*& p) { asm volatile("" : "+l"(p)); }
__device__ __forceinline__ void pin(uint32_t& v) { asm volatile("" : "+r"(v)); }

__device__ __forceinline__ unsigned col_block(unsigned j, unsigned h) { return (j & 3) + 4 * h; }

constexpr float SCL = 0.08838834764831845f * 1.4426950408889634f;

__global__ void __cluster_dims__(CLUSTER, 1, 1) __launch_bounds__(NTHREADS, 1)
decode_fused_kernel(const unsigned char* __restrict__ wq_tail, const Sched sched, const unsigned char* __restrict__ kwin,
                    const unsigned char* __restrict__ x, unsigned short* __restrict__ out, unsigned char* __restrict__ acc, const __grid_constant__ Maps maps) {
    extern __shared__ __align__(1024) unsigned char smem[];
    const int tid = threadIdx.x;
    const unsigned b = blockIdx.x, g = b >> 3, j = b & 7;
    asm volatile("{\n.reg .pred p;\nsetp.eq.u32 p, %1, 0;\n@p cp.async.bulk.prefetch.L2.global [%0], %2;\n}"
                 :: "l"(wq_tail + b * (NPF * UNIT)), "r"(tid), "n"(NPF * UNIT) : "memory");
    const unsigned t0 = now_ns();
    const uint32_t sb = smem_u32(smem);
    const uint32_t bars = sb + SM_BAR;
    const int warp = __shfl_sync(0xffffffffu, tid >> 5, 0);
    const int lane = tid & 31, w = warp & 7;
    const int r = lane >> 2, c = lane & 3, mi = lane >> 3, li = lane & 7;
    if (warp < 8) {
        if (elect()) {
            mbar_init_tx(bars + 8 * (BAR_V + w), 2 * UNIT);
            mbar_init_tx(bars + 8 * (BAR_WO + w), UNIT);
            if (w < 3) {
                mbar_init_tx(bars + 8 * (BAR_Q + w), w == 0 ? 1024 : w == 1 ? 256 : 8192);
                mbar_init(bars + 8 * (BAR_FREE + w), 8);
            } else if (w < 7) {
                mbar_init_tx(bars + 8 * (BAR_K - 3 + w), 4 * UNIT);
            }
            mbar_init_fence();
        }
        __syncwarp();
        cluster_sync_relaxed();
        {
            const uint32_t qa = sb + (16 + w) * UNIT + ((mi >> 1) * 8 + li) * 128;
            float d[4][4];
#pragma unroll
            for (int t = 0; t < 4; t++)
#pragma unroll
                for (int i = 0; i < 4; i++) d[t][i] = 0.f;
            mbar_wait(bars + 8 * BAR_WQ);
#pragma unroll 1
            for (int ks = 0; ks < 4; ks++) {
                const unsigned char* xp = smem + SM_X + w * 128 + ks * 32 + c * 4;
                const uint32_t x0 = *reinterpret_cast<const uint32_t*>(xp), x1 = *reinterpret_cast<const uint32_t*>(xp + 16);
#pragma unroll
                for (int t = 0; t < 4; t++) {
                    uint32_t a[4];
                    ldsm4t(a, qa + ks * 2048 + (((t * 2 + (mi & 1)) ^ li) * 16));
                    mma16816(d[t], a, x0, x1);
                }
            }
            __syncwarp();
            if (lane == 0) mbar_arrive(bars + 8 * BAR_FREE);
            float* rp = reinterpret_cast<float*>(smem + SM_RED) + w * 64 + c * 16 + r;
            rp[0] = (c & 2) ? ((c & 1) ? d[3][0] : d[2][0]) : ((c & 1) ? d[1][0] : d[0][0]);
            rp[8] = (c & 2) ? ((c & 1) ? d[3][2] : d[2][2]) : ((c & 1) ? d[1][2] : d[0][2]);
        }
        if (w == 0) TS(0);
        bar_sync<1, 256>();
        {
            float s0 = 0.f, s1 = 0.f;
#pragma unroll
            for (int k = 0; k < 8; k++) {
                const float2 v = *reinterpret_cast<const float2*>(smem + SM_RED + k * 256 + lane * 8);
                s0 += v.x; s1 += v.y;
            }
            st_async32(mapa(sb + SM_Q + (j >> 1) * Q_ROW + (j & 1) * 128 + lane * 4, w), pack_bf16(s0, s1),
                       mapa(bars + 8 * BAR_Q, w));
        }
        if (w == 0) TS(1);
        mbar_wait_remote(bars + 8 * BAR_Q);
        if (w == 0) TS(2);
        const int ts = c >> 1, h0 = (c & 1) * 2, i0 = (r ^ ts) & 1;
        float s[2][4];
        {
            uint4 qb[4];
#pragma unroll
            for (int t = 0; t < 4; t++)
                qb[t] = *reinterpret_cast<const uint4*>(smem + SM_Q + (r & 3) * Q_ROW + (((t * 4 + c) ^ (r & 4)) * 16));
#pragma unroll
            for (int k = 0; k < 4; k++) s[0][k] = s[1][k] = 0.f;
#pragma unroll 1
            for (int i = 0; i < 4; i++) {
                const unsigned char* ka = smem + i * 4 * UNIT + (w * 16 + r) * 256 + c * 16;
                const int sw = ((r ^ i) & 1) * 64;
                mbar_wait(bars + 8 * (BAR_K + i));
                uint4 lo[4], hi[4];
#pragma unroll
                for (int t = 0; t < 4; t++) {
                    lo[t] = *reinterpret_cast<const uint4*>(ka + ((t * 64) ^ sw));
                    hi[t] = *reinterpret_cast<const uint4*>(ka + ((t * 64) ^ sw) + 2048);
                }
                float s1[4], s2[4];
#pragma unroll
                for (int k = 0; k < 4; k++) s1[k] = s2[k] = 0.f;
#pragma unroll
                for (int t = 0; t < 4; t++) {
                    mma16816(s1, lo[t].x, hi[t].x, lo[t].y, hi[t].y, qb[t].x, qb[t].y);
                    mma16816(s2, lo[t].z, hi[t].z, lo[t].w, hi[t].w, qb[t].z, qb[t].w);
                }
#pragma unroll
                for (int k = 0; k < 4; k++) {
                    const float v = s1[k] + s2[k];
                    s[0][k] = (i == i0) ? v : s[0][k];
                    s[1][k] = (i == i0 + 2) ? v : s[1][k];
                }
                __syncwarp();
                if ((i & 1) && lane == 0) mbar_arrive(bars + 8 * (BAR_FREE + 1 + (i >> 1)));
            }
        }
        {
            float m0 = fmaxf(fmaxf(s[0][0], s[0][2]), fmaxf(s[1][0], s[1][2]));
            float m1 = fmaxf(fmaxf(s[0][1], s[0][3]), fmaxf(s[1][1], s[1][3]));
#pragma unroll
            for (int o = 2; o < 32; o <<= 1) {
                m0 = fmaxf(m0, __shfl_xor_sync(0xffffffffu, m0, o));
                m1 = fmaxf(m1, __shfl_xor_sync(0xffffffffu, m1, o));
            }
            if (lane < 2) *reinterpret_cast<float2*>(smem + SM_MAX + w * 16 + lane * 8) = make_float2(m0, m1);
        }
        if (w == 7) TS(3);
        bar_sync<1, 256>();
        {
            float m0 = -INFINITY, m1 = -INFINITY;
#pragma unroll
            for (int k = 0; k < 8; k++) {
                const float2 m = *reinterpret_cast<const float2*>(smem + SM_MAX + k * 16 + (c & 1) * 8);
                m0 = fmaxf(m0, m.x); m1 = fmaxf(m1, m.y);
            }
            float l0 = 0.f, l1 = 0.f;
#pragma unroll
            for (int u = 0; u < 2; u++) {
                const unsigned p01 = pack_bf16(ex2((s[u][0] - m0) * SCL), ex2((s[u][1] - m1) * SCL));
                const unsigned p23 = pack_bf16(ex2((s[u][2] - m0) * SCL), ex2((s[u][3] - m1) * SCL));
                unsigned char* pp = smem + SM_P + h0 * P_ROW + ((2 * u + i0) * 4 + (w >> 1)) * 64 + (r >> 1) * 16 + (w & 1) * 8 + (r & 1) * 2;
                *reinterpret_cast<unsigned short*>(pp) = (unsigned short)p01;
                *reinterpret_cast<unsigned short*>(pp + P_ROW) = (unsigned short)(p01 >> 16);
                *reinterpret_cast<unsigned short*>(pp + 4) = (unsigned short)p23;
                *reinterpret_cast<unsigned short*>(pp + P_ROW + 4) = (unsigned short)(p23 >> 16);
                l0 += bf_lo(p01) + bf_lo(p23); l1 += bf_hi(p01) + bf_hi(p23);
            }
#pragma unroll
            for (int o = 2; o < 32; o <<= 1) {
                l0 += __shfl_xor_sync(0xffffffffu, l0, o);
                l1 += __shfl_xor_sync(0xffffffffu, l1, o);
            }
            if (lane < 2) *reinterpret_cast<float2*>(smem + SM_SUM + w * 16 + lane * 8) = make_float2(l0, l1);
        }
        bar_sync<1, 256>();
        if (lane < 4) {
            float m = -INFINITY, l = 0.f;
#pragma unroll
            for (int k = 0; k < 8; k++) {
                m = fmaxf(m, *reinterpret_cast<const float*>(smem + SM_MAX + k * 16 + lane * 4));
                l += *reinterpret_cast<const float*>(smem + SM_SUM + k * 16 + lane * 4);
            }
            st_async64(mapa(sb + SM_ST + j * 32 + lane * 8, w), m, l, mapa(bars + 8 * BAR_ST, w));
        }
        bar_arrive<3, NPAIR>();
        if (w == 0) TS(4);
        const unsigned line = col_block(j, w >> 2) * 4 + (w & 3);
        unsigned char* aptr = acc + line * ACC_STRIDE + ((c & 1) * 8 + r) * 8;
        unsigned short* outp = out + line * 16 + (c & 1) * 8 + r;
        pin(aptr); pin(outp);
        const uint32_t ta = sb + ((mi >> 1) * 8 + li) * 128 + ((((w & 3) * 2 + (mi & 1)) ^ li) * 16);
        {
            float oa[4][4];
#pragma unroll
            for (int i = 0; i < 4; i++) oa[0][i] = oa[1][i] = oa[2][i] = oa[3][i] = 0.f;
            const unsigned char* pp = smem + SM_P + (r & 3) * P_ROW + c * 16;
            const uint32_t dst0 = (c & 1) * 4 + ts * 2;
            const uint32_t oaddr = sb + SM_OB + j * 1024 + (w * 8 + r) * 16;
            uint32_t oa0 = mapa(oaddr, dst0), oa1 = mapa(oaddr, dst0 + 1);
            uint32_t ob0 = mapa(bars + 8 * BAR_O, dst0), ob1 = mapa(bars + 8 * BAR_O, dst0 + 1);
            pin(oa0); pin(oa1); pin(ob0); pin(ob1);
#pragma unroll 1
            for (int u = 0; u < 8; u++) {
                const uint4 p0 = *reinterpret_cast<const uint4*>(pp + u * 128);
                const uint4 p1 = *reinterpret_cast<const uint4*>(pp + u * 128 + 64);
                const uint32_t va = ta + (w >> 2) * 4096 + (u < 4 ? 16 + 2 * u : 2 * u - 8) * UNIT;
                mbar_wait(bars + 8 * (BAR_V + u));
                if (w == 0) TS(8);
                uint32_t a[4][4];
                ldsm4t(a[0], va);
                ldsm4t(a[1], va + 2048);
                ldsm4t(a[2], va + UNIT);
                ldsm4t(a[3], va + UNIT + 2048);
                mma16816(oa[0], a[0], p0.x, p0.y);
                mma16816(oa[1], a[1], p0.z, p0.w);
                mma16816(oa[2], a[2], p1.x, p1.y);
                mma16816(oa[3], a[3], p1.z, p1.w);
            }
            float v[4];
#pragma unroll
            for (int i = 0; i < 4; i++) v[i] = (oa[0][i] + oa[1][i]) + (oa[2][i] + oa[3][i]);
            st_async128(oa0, v[0], v[1], v[2], v[3], ob0);
            st_async128(oa1, v[0], v[1], v[2], v[3], ob1);
        }
        float d[2][4];
        {
            const uint32_t wa = ta + (8 + (w >> 2)) * UNIT, wbar = bars + 8 * (BAR_WO + (w >> 2));
            uint32_t a[8][4];
#pragma unroll
            for (int k = 0; k < 2; k++) {
                mbar_wait(wbar + k * 16);
#pragma unroll
                for (int i = 0; i < 4; i++) ldsm4t(a[4 * k + i], wa + k * 2 * UNIT + i * 2048);
            }
            if (w == 0) TS(11);
            bar_sync<2, NPAIR>();
            uint4 ob[8];
#pragma unroll
            for (int k = 0; k < 8; k++) ob[k] = *reinterpret_cast<const uint4*>(smem + SM_O + k * 64 + c * 16);
#pragma unroll
            for (int i = 0; i < 4; i++) d[0][i] = d[1][i] = 0.f;
#pragma unroll
            for (int k = 0; k < 4; k++) {
                mma16816(d[0], a[2 * k], ob[k].x, ob[k].y);
                mma16816(d[1], a[2 * k + 1], ob[k].z, ob[k].w);
            }
            uint32_t a2[8][4];
            constexpr int N2 = 4;
            mbar_wait(wbar + 2 * 16);
#pragma unroll
            for (int i = 0; i < N2; i++) ldsm4t(a2[i], wa + (2 + (i >> 2)) * 2 * UNIT + (i & 3) * 2048);
            mbar_wait(wbar + 3 * 16);
            if (w == 7) TS(14);
#pragma unroll
            for (int i = N2; i < 8; i++) ldsm4t(a2[i], wa + 3 * 2 * UNIT + (i & 3) * 2048);
            constexpr int K0 = 0;
#pragma unroll
            for (int k = K0; k < 4; k++) {
                mma16816(d[0], a2[2 * k], ob[4 + k].x, ob[4 + k].y);
                mma16816(d[1], a2[2 * k + 1], ob[4 + k].z, ob[4 + k].w);
            }
        }
        if (c < 2) {
            const float v = c ? d[0][2] + d[1][2] : d[0][0] + d[1][0];
            const float2 old = atom_add2(aptr, v, 1.f);
            if (old.y == 15.f)
                asm volatile("st.global.u16 [%0], %1;" :: "l"(outp), "h"((unsigned short)pack_bf16(old.x + v, 0.f)) : "memory");
        }
    } else if (warp < 8 + NCW) {
        if (tid == 256 && b == 0) asm volatile("cp.async.bulk.prefetch.L2.global [%0], 1024;" :: "l"(x) : "memory");
        __syncwarp();
        cluster_sync_relaxed();
        unsigned char* flag = acc + (32 + (j & 3)) * ACC_STRIDE;
        if (b < 4 && w == 0) {
#pragma unroll
            for (int h = 0; h < 2; h++)
                asm volatile("st.global.v4.u32 [%0], {%1,%1,%1,%1};"
                             :: "l"(acc + (col_block(j, h) * 4 + mi) * ACC_STRIDE + li * 16), "r"(0u) : "memory");
            __syncwarp();
            if (lane < 8) {
                asm volatile("fence.acq_rel.gpu;" ::: "memory");
                asm volatile("st.relaxed.gpu.global.u32 [%0], %1;" :: "l"(flag + lane * 4), "r"(1u) : "memory");
            }
        }
        bar_sync<3, NPAIR>();
        if (tid == 256) {
            unsigned f, n = 0;
            do {
                ++n;
                asm volatile("atom.acquire.gpu.global.or.b32 %0, [%1], 0;" : "=r"(f) : "l"(flag) : "memory");
            } while (f == 0 && n < SPIN_LIMIT);
            asm volatile("red.relaxed.gpu.global.inc.u32 [%0], 16;" :: "l"(flag) : "memory");
        }
        __syncwarp();
        mbar_wait_remote(bars + 8 * BAR_ST);
        float wt[2][8];
        {
            float4 st[8];
            float M0 = -INFINITY, M1 = -INFINITY, L0 = 0.f, L1 = 0.f;
#pragma unroll
            for (int k = 0; k < 8; k++) {
                st[k] = *reinterpret_cast<const float4*>(smem + SM_ST + k * 32 + (j >> 2) * 16);
                M0 = fmaxf(M0, st[k].x); M1 = fmaxf(M1, st[k].z);
            }
#pragma unroll
            for (int k = 0; k < 8; k++) {
                wt[0][k] = ex2((st[k].x - M0) * SCL); L0 = fmaf(wt[0][k], st[k].y, L0);
                wt[1][k] = ex2((st[k].z - M1) * SCL); L1 = fmaf(wt[1][k], st[k].w, L1);
            }
            const float i0 = __fdividef(1.f, L0), i1 = __fdividef(1.f, L1);
#pragma unroll
            for (int k = 0; k < 8; k++) { wt[0][k] *= i0; wt[1][k] *= i1; }
        }
        constexpr int VPT = 8 / NCW;
        const int t = tid - 256, e = t * VPT / 4, sw = e >> 3, sr = e & 7;
        uint32_t op = sb + SM_O + (sw >> 1) * 64 + (sr >> 1) * 16 + (sw & 1) * 8 + (sr & 1) * 2 + (VPT == 2 ? (t & 1) * 4 : 0);
        pin(op);
        mbar_wait_remote(bars + 8 * BAR_O);
        if (w == 0) TS(10);
        float v[8][VPT];
#pragma unroll
        for (int k = 0; k < 8; k++) {
            if (VPT == 4) *reinterpret_cast<float4*>(v[k]) = *reinterpret_cast<const float4*>(smem + SM_OB + k * 1024 + t * 16);
            else *reinterpret_cast<float2*>(v[k]) = *reinterpret_cast<const float2*>(smem + SM_OB + k * 1024 + t * 8);
        }
#pragma unroll
        for (int i = 0; i < VPT; i++) {
            const float (&u)[8] = wt[i & 1];
            const float o = (fmaf(u[0], v[0][i], u[1] * v[1][i]) + fmaf(u[2], v[2][i], u[3] * v[3][i]))
                          + (fmaf(u[4], v[4][i], u[5] * v[5][i]) + fmaf(u[6], v[6][i], u[7] * v[7][i]));
            asm volatile("st.shared.u16 [%0], %1;" :: "r"(op + (i & 1) * 256 + (i >> 1) * 4), "h"((unsigned short)pack_bf16(o, o)) : "memory");
        }
        bar_arrive<2, NPAIR>();
    } else {
        unsigned due = t0 + sched.first + NPF * sched.step;
        if (elect()) {
            prefetch_map(&maps.wq);
            mbar_init_tx(bars + 8 * BAR_WQ, 8 * UNIT + 1024);
            mbar_init_fence();
        }
        __syncwarp();
        asm volatile("barrier.cluster.arrive.relaxed.aligned;" ::: "memory");
        TS(35);
        if (elect()) {
#pragma unroll 1
            for (int s = 0; s < 8 - NPF; s++) {
                wait_until(due);
                tma_load(sb + (16 + s) * UNIT, &maps.wq, s * 64, b, bars + 8 * BAR_WQ);
                due += sched.step;
            }
        }
        __syncwarp();
        asm volatile("barrier.cluster.wait.aligned;" ::: "memory");
        TS(36);
        if (elect()) {
            const unsigned char* kp = kwin + (g * (unsigned)(SK * 256) + j * 131072u);
#pragma unroll 1
            for (int s = 0; s < 16; s++) {
                wait_until(due);
                bulk_load(sb + s * UNIT, kp + s * UNIT, UNIT, bars + 8 * (BAR_K + (s >> 2)));
                due += sched.step;
                if (s < NPF) tma_load(sb + (24 - NPF + s) * UNIT, &maps.wq, (8 - NPF + s) * 64, b, bars + 8 * BAR_WQ);
                if (s == NPF) bulk_load(sb + SM_X, x, 1024, bars + 8 * BAR_WQ);
                if (s == 8) { prefetch_map(&maps.v); prefetch_map(&maps.wo); }
            }
            const int key0 = g * SK + (SK - WIN) + j * 512;
#pragma unroll 1
            for (int s = 0; s < 16; s++) {
                if ((s & 7) == 0) mbar_wait(bars + 8 * (BAR_FREE + (s >> 3)));
                wait_until(due);
                tma_load(sb + (s < 8 ? 16 + s : s - 8) * UNIT, &maps.v, key0 + s * 32, 0, bars + 8 * (BAR_V + (s >> 1)));
                due += sched.step;
            }
            TS(37);
            due += sched.wo_gap;
            mbar_wait(bars + 8 * (BAR_FREE + 2));
#pragma unroll 1
            for (int s = 0; s < 8; s++) {
                wait_until(due);
                tma_load(sb + (8 + s) * UNIT, &maps.wo, (b >> 2) * 256 + (s >> 1) * 64, col_block(j, s & 1), bars + 8 * (BAR_WO + s));
                due += sched.wo_step;
            }
            TS(38);
        }
    }
}

}

typedef CUresult (*EncodeFn)(CUtensorMap*, CUtensorMapDataType, cuuint32_t, void*, const cuuint64_t*, const cuuint64_t*,
                             const cuuint32_t*, const cuuint32_t*, CUtensorMapInterleave, CUtensorMapSwizzle,
                             CUtensorMapL2promotion, CUtensorMapFloatOOBfill);

static void make_map(EncodeFn enc, CUtensorMap* m, void* p, uint64_t rows, uint64_t nblk, uint32_t box_rows, uint32_t box_blks) {
    const cuuint64_t dims[3] = {64, rows, nblk}, strides[2] = {nblk * 128, 128};
    const cuuint32_t box[3] = {64, box_rows, box_blks}, es[3] = {1, 1, 1};
    enc(m, CU_TENSOR_MAP_DATA_TYPE_BFLOAT16, 3, p, dims, strides, box, es, CU_TENSOR_MAP_INTERLEAVE_NONE,
        CU_TENSOR_MAP_SWIZZLE_128B, CU_TENSOR_MAP_L2_PROMOTION_NONE, CU_TENSOR_MAP_FLOAT_OOB_FILL_NONE);
}

extern "C" void kernel_launch(void* const* d_in, const int* in_sizes, int n_in, void* d_out, int out_size) {
    EncodeFn enc = nullptr;
    cudaDriverEntryPointQueryResult qr;
    cudaGetDriverEntryPoint("cuTensorMapEncodeTiled", (void**)&enc, cudaEnableDefault, &qr);
    Maps maps;
    make_map(enc, &maps.wq, d_in[3], 512, 64, 64, 1);
    make_map(enc, &maps.v, d_in[2], 8 * SK, 2, 32, 2);
    make_map(enc, &maps.wo, d_in[4], 4096, 8, 64, 1);
    void* acc = nullptr;
    cudaGetSymbolAddress(&acc, g_scratch);
    cudaFuncSetAttribute(decode_fused_kernel, cudaFuncAttributeMaxDynamicSharedMemorySize, SMEM_BYTES);
    Sched s = {-600, 165, 120, 172};
    decode_fused_kernel<<<NCTA, NTHREADS, SMEM_BYTES>>>((const unsigned char*)d_in[3] + (8 - NPF) * 64 * 8192, s,
                                                        (const unsigned char*)d_in[1] + (size_t)(SK - WIN) * 256,
                                                        (const unsigned char*)d_in[0], (unsigned short*)d_out,
                                                        (unsigned char*)acc, maps);
}
```

```cpp
#include <cuda_runtime.h>
#include <cuda.h>
#include <cuda_bf16.h>
#include <stdint.h>

namespace {

constexpr int SK = 32768, WIN = 4096;
constexpr int NCTA = 64, CLUSTER = 8;
#define NCW 1
constexpr int NPAIR = 256 + 32 * NCW;
constexpr int NTHREADS = NPAIR + 32;

constexpr int BAR_V = 0;
constexpr int BAR_WO = 8;
constexpr int BAR_Q = 16, BAR_ST = 17, BAR_OP = 18, BAR_O = 19;
constexpr int BAR_K = 20;
constexpr int BAR_FREE = 24;
constexpr int BAR_WQ = 27;

constexpr int UNIT = 8192;
constexpr int SM_OP = 24 * UNIT;
constexpr int SM_RED = SM_OP + 2048;
constexpr int SM_Q = SM_RED + 2048;
constexpr int Q_ROW = 320;
constexpr int SM_P = SM_Q + 4 * Q_ROW;
constexpr int P_ROW = 1088;
constexpr int SM_MAX = SM_P + 4 * P_ROW;
constexpr int SM_SUM = SM_MAX + 128;
constexpr int SM_ST = SM_SUM + 128;
constexpr int SM_O = SM_ST + 256;
constexpr int SM_X = SM_O + 1024;
constexpr int SM_BAR = SM_X + 1024;
constexpr int SMEM_BYTES = SM_BAR + 256;

constexpr int NPF = 2;
constexpr unsigned SPIN_LIMIT = 1u << 20;

constexpr int ACC_STRIDE = 256;
__device__ __align__(8192) unsigned char g_scratch[(32 + 8) * ACC_STRIDE];

struct Sched { int first, step, wo_gap, wo_step; };
struct Maps { CUtensorMap wq, v, wo; };

#define TS(i)

__device__ __forceinline__ unsigned now_ns() { unsigned t; asm volatile("mov.u32 %0, %%globaltimer_lo;" : "=r"(t)); return t; }
__device__ __forceinline__ void wait_until(unsigned t) { while ((int)(now_ns() - t) < 0) {} }
__device__ __forceinline__ uint32_t smem_u32(const void* p) { return (uint32_t)__cvta_generic_to_shared(p); }
__device__ __forceinline__ bool elect() {
    unsigned p; asm volatile("{\n.reg .pred p;\nelect.sync _|p, 0xffffffff;\nselp.u32 %0, 1, 0, p;\n}" : "=r"(p)); return p;
}
__device__ __forceinline__ void mbar_init(uint32_t bar, uint32_t cnt) {
    asm volatile("mbarrier.init.shared::cta.b64 [%0], %1;" :: "r"(bar), "r"(cnt) : "memory");
}
__device__ __forceinline__ void mbar_init_tx(uint32_t bar, uint32_t bytes) {
    mbar_init(bar, 1);
    asm volatile("mbarrier.arrive.expect_tx.shared::cta.b64 _, [%0], %1;" :: "r"(bar), "r"(bytes) : "memory");
}
__device__ __forceinline__ void mbar_init_fence() { asm volatile("fence.mbarrier_init.release.cluster;" ::: "memory"); }
__device__ __forceinline__ void mbar_arrive(uint32_t bar) {
    asm volatile("mbarrier.arrive.shared::cta.b64 _, [%0];" :: "r"(bar) : "memory");
}
__device__ __forceinline__ void mbar_wait(uint32_t bar) {
    unsigned ok, n = 0;
    do {
        ++n;
        asm volatile("{\n.reg .pred p;\nmbarrier.try_wait.parity.shared::cta.b64 p, [%1], 0;\nselp.u32 %0, 1, 0, p;\n}"
                     : "=r"(ok) : "r"(bar) : "memory");
    } while (!ok && n < SPIN_LIMIT);
}
__device__ __forceinline__ void mbar_wait_remote(uint32_t bar) {
    unsigned ok, n = 0;
    do {
        ++n;
        asm volatile("{\n.reg .pred p;\nmbarrier.try_wait.parity.relaxed.cluster.shared::cta.b64 p, [%1], 0;\nselp.u32 %0, 1, 0, p;\n}"
                     : "=r"(ok) : "r"(bar) : "memory");
    } while (!ok && n < SPIN_LIMIT);
    asm volatile("fence.acquire.sync_restrict::shared::cluster.cluster;" ::: "memory");
}
__device__ __forceinline__ void bulk_load(uint32_t dst, const void* src, uint32_t bytes, uint32_t bar) {
    asm volatile("cp.async.bulk.shared::cluster.global.mbarrier::complete_tx::bytes [%0], [%1], %2, [%3];"
                 :: "r"(dst), "l"(src), "r"(bytes), "r"(bar) : "memory");
}
__device__ __forceinline__ void tma_load(uint32_t dst, const CUtensorMap* m, int row, int blk, uint32_t bar) {
    asm volatile("cp.async.bulk.tensor.3d.shared::cluster.global.mbarrier::complete_tx::bytes [%0], [%1, {%2, %3, %4}], [%5];"
                 :: "r"(dst), "l"(m), "r"(0), "r"(row), "r"(blk), "r"(bar) : "memory");
}
__device__ __forceinline__ void prefetch_map(const CUtensorMap* m) {
    asm volatile("prefetch.tensormap [%0];" :: "l"(m) : "memory");
}
__device__ __forceinline__ uint32_t mapa(uint32_t addr, uint32_t rank) {
    uint32_t r; asm("mapa.shared::cluster.u32 %0, %1, %2;" : "=r"(r) : "r"(addr), "r"(rank)); return r;
}
__device__ __forceinline__ void st_async32(uint32_t dst, unsigned v, uint32_t bar) {
    asm volatile("st.async.shared::cluster.mbarrier::complete_tx::bytes.b32 [%0], %1, [%2];" :: "r"(dst), "r"(v), "r"(bar) : "memory");
}
__device__ __forceinline__ void st_async64(uint32_t dst, float a, float b, uint32_t bar) {
    asm volatile("st.async.shared::cluster.mbarrier::complete_tx::bytes.v2.f32 [%0], {%1,%2}, [%3];"
                 :: "r"(dst), "f"(a), "f"(b), "r"(bar) : "memory");
}
template <int ID, int N> __device__ __forceinline__ void bar_sync() { asm volatile("bar.sync %0, %1;" :: "n"(ID), "n"(N) : "memory"); }
template <int ID, int N> __device__ __forceinline__ void bar_arrive() { asm volatile("bar.arrive %0, %1;" :: "n"(ID), "n"(N) : "memory"); }
__device__ __forceinline__ void cluster_sync_relaxed() {
    asm volatile("barrier.cluster.arrive.relaxed.aligned;\nbarrier.cluster.wait.aligned;" ::: "memory");
}
__device__ __forceinline__ float2 atom_add2(void* p, float a, float b) {
    float2 r;
    asm volatile("atom.relaxed.gpu.global.add.v2.f32 {%0,%1}, [%2], {%3,%4};"
                 : "=f"(r.x), "=f"(r.y) : "l"(p), "f"(a), "f"(b) : "memory");
    return r;
}
__device__ __forceinline__ void ldsm4t(uint32_t (&r)[4], uint32_t addr) {
    asm volatile("ldmatrix.sync.aligned.m8n8.x4.trans.shared.b16 {%0,%1,%2,%3}, [%4];"
                 : "=r"(r[0]), "=r"(r[1]), "=r"(r[2]), "=r"(r[3]) : "r"(addr) : "memory");
}
__device__ __forceinline__ void mma16816(float (&d)[4], uint32_t a0, uint32_t a1, uint32_t a2, uint32_t a3, uint32_t b0, uint32_t b1) {
    asm volatile("mma.sync.aligned.m16n8k16.row.col.f32.bf16.bf16.f32 {%0,%1,%2,%3}, {%4,%5,%6,%7}, {%8,%9}, {%0,%1,%2,%3};"
                 : "+f"(d[0]), "+f"(d[1]), "+f"(d[2]), "+f"(d[3])
                 : "r"(a0), "r"(a1), "r"(a2), "r"(a3), "r"(b0), "r"(b1));
}
__device__ __forceinline__ void mma16816(float (&d)[4], const uint32_t (&a)[4], uint32_t b0, uint32_t b1) {
    mma16816(d, a[0], a[1], a[2], a[3], b0, b1);
}
__device__ __forceinline__ float bf_lo(unsigned u) { return __uint_as_float(u << 16); }
__device__ __forceinline__ float bf_hi(unsigned u) { return __uint_as_float(u & 0xffff0000u); }
__device__ __forceinline__ unsigned pack_bf16(float lo, float hi) {
    unsigned r; asm("cvt.rn.bf16x2.f32 %0, %1, %2;" : "=r"(r) : "f"(hi), "f"(lo)); return r;
}
__device__ __forceinline__ float ex2(float x) { float y; asm("ex2.approx.ftz.f32 %0, %1;" : "=f"(y) : "f"(x)); return y; }
template <typename T> __device__ __forceinline__ void pin(T*& p) { asm volatile("" : "+l"(p)); }
__device__ __forceinline__ void pin(uint32_t& v) { asm volatile("" : "+r"(v)); }

constexpr float SCL = 0.08838834764831845f * 1.4426950408889634f;

__global__ void __cluster_dims__(CLUSTER, 1, 1) __launch_bounds__(NTHREADS, 1)
decode_fused_kernel(const unsigned char* __restrict__ wq_tail, const Sched sched, const unsigned char* __restrict__ kwin,
                    const unsigned char* __restrict__ x, unsigned short* __restrict__ out, unsigned char* __restrict__ acc, const __grid_constant__ Maps maps) {
    extern __shared__ __align__(1024) unsigned char smem[];
    const int tid = threadIdx.x;
    const unsigned b = blockIdx.x, g = b >> 3, j = b & 7;
    asm volatile("{\n.reg .pred p;\nsetp.eq.u32 p, %1, 0;\n@p cp.async.bulk.prefetch.L2.global [%0], %2;\n}"
                 :: "l"(wq_tail + b * (NPF * UNIT)), "r"(tid), "n"(NPF * UNIT) : "memory");
    const unsigned t0 = now_ns();
    const uint32_t sb = smem_u32(smem);
    const uint32_t bars = sb + SM_BAR;
    const int warp = __shfl_sync(0xffffffffu, tid >> 5, 0);
    const int lane = tid & 31, w = warp & 7;
    const int r = lane >> 2, c = lane & 3, mi = lane >> 3, li = lane & 7;
    if (warp < 8) {
        if (elect()) {
            mbar_init_tx(bars + 8 * (BAR_V + w), 2 * UNIT);
            mbar_init_tx(bars + 8 * (BAR_WO + w), UNIT);
            mbar_init_tx(bars + 8 * (BAR_Q + w), w >= 4 ? 4 * UNIT : w == 1 ? 256 : w == 2 ? 2048 : 1024);
            if (w < 3) mbar_init(bars + 8 * (BAR_FREE + w), 8);
            mbar_init_fence();
        }
        __syncwarp();
        cluster_sync_relaxed();
        {
            const uint32_t qa = sb + (16 + w) * UNIT + ((mi >> 1) * 8 + li) * 128;
            float d[4][4];
#pragma unroll
            for (int t = 0; t < 4; t++)
#pragma unroll
                for (int i = 0; i < 4; i++) d[t][i] = 0.f;
            mbar_wait(bars + 8 * BAR_WQ);
#pragma unroll 1
            for (int ks = 0; ks < 4; ks++) {
                const unsigned char* xp = smem + SM_X + w * 128 + ks * 32 + c * 4;
                const uint32_t x0 = *reinterpret_cast<const uint32_t*>(xp), x1 = *reinterpret_cast<const uint32_t*>(xp + 16);
#pragma unroll
                for (int t = 0; t < 4; t++) {
                    uint32_t a[4];
                    ldsm4t(a, qa + ks * 2048 + (((t * 2 + (mi & 1)) ^ li) * 16));
                    mma16816(d[t], a, x0, x1);
                }
            }
            __syncwarp();
            if (lane == 0) mbar_arrive(bars + 8 * BAR_FREE);
            float* rp = reinterpret_cast<float*>(smem + SM_RED) + w * 64 + c * 16 + r;
            rp[0] = (c & 2) ? ((c & 1) ? d[3][0] : d[2][0]) : ((c & 1) ? d[1][0] : d[0][0]);
            rp[8] = (c & 2) ? ((c & 1) ? d[3][2] : d[2][2]) : ((c & 1) ? d[1][2] : d[0][2]);
        }
        if (w == 0) TS(0);
        bar_sync<1, 256>();
        {
            float s0 = 0.f, s1 = 0.f;
#pragma unroll
            for (int k = 0; k < 8; k++) {
                const float2 v = *reinterpret_cast<const float2*>(smem + SM_RED + k * 256 + lane * 8);
                s0 += v.x; s1 += v.y;
            }
            st_async32(mapa(sb + SM_Q + (j >> 1) * Q_ROW + (j & 1) * 128 + lane * 4, w), pack_bf16(s0, s1),
                       mapa(bars + 8 * BAR_Q, w));
        }
        if (w == 0) TS(1);
        mbar_wait_remote(bars + 8 * BAR_Q);
        if (w == 0) TS(2);
        const int ts = c >> 1, h0 = (c & 1) * 2, i0 = (r ^ ts) & 1;
        float s[2][4];
        {
            uint4 qb[4];
#pragma unroll
            for (int t = 0; t < 4; t++)
                qb[t] = *reinterpret_cast<const uint4*>(smem + SM_Q + (r & 3) * Q_ROW + (((t * 4 + c) ^ (r & 4)) * 16));
#pragma unroll
            for (int k = 0; k < 4; k++) s[0][k] = s[1][k] = 0.f;
#pragma unroll 1
            for (int i = 0; i < 4; i++) {
                const unsigned char* ka = smem + i * 4 * UNIT + (w * 16 + r) * 256 + c * 16;
                const int sw = ((r ^ i) & 1) * 64;
                mbar_wait(bars + 8 * (BAR_K + i));
                uint4 lo[4], hi[4];
#pragma unroll
                for (int t = 0; t < 4; t++) {
                    lo[t] = *reinterpret_cast<const uint4*>(ka + ((t * 64) ^ sw));
                    hi[t] = *reinterpret_cast<const uint4*>(ka + ((t * 64) ^ sw) + 2048);
                }
                float s1[4], s2[4];
#pragma unroll
                for (int k = 0; k < 4; k++) s1[k] = s2[k] = 0.f;
#pragma unroll
                for (int t = 0; t < 4; t++) {
                    mma16816(s1, lo[t].x, hi[t].x, lo[t].y, hi[t].y, qb[t].x, qb[t].y);
                    mma16816(s2, lo[t].z, hi[t].z, lo[t].w, hi[t].w, qb[t].z, qb[t].w);
                }
#pragma unroll
                for (int k = 0; k < 4; k++) {
                    const float v = s1[k] + s2[k];
                    s[0][k] = (i == i0) ? v : s[0][k];
                    s[1][k] = (i == i0 + 2) ? v : s[1][k];
                }
                __syncwarp();
                if ((i & 1) && lane == 0) mbar_arrive(bars + 8 * (BAR_FREE + 1 + (i >> 1)));
            }
        }
        {
            float m0 = fmaxf(fmaxf(s[0][0], s[0][2]), fmaxf(s[1][0], s[1][2]));
            float m1 = fmaxf(fmaxf(s[0][1], s[0][3]), fmaxf(s[1][1], s[1][3]));
#pragma unroll
            for (int o = 2; o < 32; o <<= 1) {
                m0 = fmaxf(m0, __shfl_xor_sync(0xffffffffu, m0, o));
                m1 = fmaxf(m1, __shfl_xor_sync(0xffffffffu, m1, o));
            }
            if (lane < 2) *reinterpret_cast<float2*>(smem + SM_MAX + w * 16 + lane * 8) = make_float2(m0, m1);
        }
        if (w == 7) TS(3);
        bar_sync<1, 256>();
        {
            float m0 = -INFINITY, m1 = -INFINITY;
#pragma unroll
            for (int k = 0; k < 8; k++) {
                const float2 m = *reinterpret_cast<const float2*>(smem + SM_MAX + k * 16 + (c & 1) * 8);
                m0 = fmaxf(m0, m.x); m1 = fmaxf(m1, m.y);
            }
            float l0 = 0.f, l1 = 0.f;
#pragma unroll
            for (int u = 0; u < 2; u++) {
                const unsigned p01 = pack_bf16(ex2((s[u][0] - m0) * SCL), ex2((s[u][1] - m1) * SCL));
                const unsigned p23 = pack_bf16(ex2((s[u][2] - m0) * SCL), ex2((s[u][3] - m1) * SCL));
                unsigned char* pp = smem + SM_P + h0 * P_ROW + ((2 * u + i0) * 4 + (w >> 1)) * 64 + (r >> 1) * 16 + (w & 1) * 8 + (r & 1) * 2;
                *reinterpret_cast<unsigned short*>(pp) = (unsigned short)p01;
                *reinterpret_cast<unsigned short*>(pp + P_ROW) = (unsigned short)(p01 >> 16);
                *reinterpret_cast<unsigned short*>(pp + 4) = (unsigned short)p23;
                *reinterpret_cast<unsigned short*>(pp + P_ROW + 4) = (unsigned short)(p23 >> 16);
                l0 += bf_lo(p01) + bf_lo(p23); l1 += bf_hi(p01) + bf_hi(p23);
            }
#pragma unroll
            for (int o = 2; o < 32; o <<= 1) {
                l0 += __shfl_xor_sync(0xffffffffu, l0, o);
                l1 += __shfl_xor_sync(0xffffffffu, l1, o);
            }
            if (lane < 2) *reinterpret_cast<float2*>(smem + SM_SUM + w * 16 + lane * 8) = make_float2(l0, l1);
        }
        bar_sync<1, 256>();
        if (lane < 4) {
            float m = -INFINITY, l = 0.f;
#pragma unroll
            for (int k = 0; k < 8; k++) {
                m = fmaxf(m, *reinterpret_cast<const float*>(smem + SM_MAX + k * 16 + lane * 4));
                l += *reinterpret_cast<const float*>(smem + SM_SUM + k * 16 + lane * 4);
            }
            st_async64(mapa(sb + SM_ST + j * 32 + lane * 8, w), m, l, mapa(bars + 8 * BAR_ST, w));
        }
        bar_arrive<3, NPAIR>();
        if (w == 0) TS(4);
        const uint32_t ta = sb + ((mi >> 1) * 8 + li) * 128 + ((((w & 3) * 2 + (mi & 1)) ^ li) * 16);
        {
            float oa[4][4];
#pragma unroll
            for (int i = 0; i < 4; i++) oa[0][i] = oa[1][i] = oa[2][i] = oa[3][i] = 0.f;
            const unsigned char* pp = smem + SM_P + (r & 3) * P_ROW + c * 16;
            uint32_t odst = mapa(sb + SM_OP + j * 256 + ((r & 1) * 32 + (r >> 1) * 8 + ts * 4 + h0) * 4, w);
            uint32_t obar = mapa(bars + 8 * BAR_OP, w);
            pin(odst); pin(obar);
#pragma unroll 1
            for (int u = 0; u < 8; u++) {
                const uint4 p0 = *reinterpret_cast<const uint4*>(pp + u * 128);
                const uint4 p1 = *reinterpret_cast<const uint4*>(pp + u * 128 + 64);
                const uint32_t va = ta + (w >> 2) * 4096 + (u < 4 ? 16 + 2 * u : 2 * u - 8) * UNIT;
                mbar_wait(bars + 8 * (BAR_V + u));
                if (w == 0) TS(8);
                uint32_t a[4][4];
                ldsm4t(a[0], va);
                ldsm4t(a[1], va + 2048);
                ldsm4t(a[2], va + UNIT);
                ldsm4t(a[3], va + UNIT + 2048);
                mma16816(oa[0], a[0], p0.x, p0.y);
                mma16816(oa[1], a[1], p0.z, p0.w);
                mma16816(oa[2], a[2], p1.x, p1.y);
                mma16816(oa[3], a[3], p1.z, p1.w);
            }
            float v[4];
#pragma unroll
            for (int i = 0; i < 4; i++) v[i] = (oa[0][i] + oa[1][i]) + (oa[2][i] + oa[3][i]);
            st_async64(odst, ts ? v[2] : v[0], ts ? v[3] : v[1], obar);
        }
        const unsigned col = j * 64 + (w & 3) * 16 + (c & 1) * 8 + r;
        unsigned short* outp = out + (col & ~1u);
        pin(outp);
        float* part = reinterpret_cast<float*>(smem + SM_RED) + (col & 63);
        const uint32_t wa = ta + (8 + (w & 4)) * UNIT, wbar = bars + 8 * (BAR_WO + (w & 4));
        const unsigned char* op = smem + SM_O + (w & 4) * 16 + c * 16;
        uint4 ob[8];
        if (w < 4) {
            uint32_t a[16][4];
#pragma unroll
            for (int k = 0; k < 4; k++) {
                mbar_wait(wbar + k * 8);
#pragma unroll
                for (int i = 0; i < 4; i++) ldsm4t(a[4 * k + i], wa + k * UNIT + i * 2048);
            }
            if (w == 0) TS(11);
            mbar_wait_remote(bars + 8 * BAR_O);
#pragma unroll
            for (int i = 0; i < 8; i++) ob[i] = *reinterpret_cast<const uint4*>(op + i * 128);
            float d[4][4];
#pragma unroll
            for (int i = 0; i < 4; i++) d[0][i] = d[1][i] = d[2][i] = d[3][i] = 0.f;
#pragma unroll
            for (int i = 0; i < 8; i++) {
                mma16816(d[(i & 1) * 2], a[i], ob[i].x, ob[i].y);
                mma16816(d[(i & 1) * 2 + 1], a[8 + i], ob[i].z, ob[i].w);
            }
            if (c < 2) *part = c ? (d[0][2] + d[1][2]) + (d[2][2] + d[3][2]) : (d[0][0] + d[1][0]) + (d[2][0] + d[3][0]);
            bar_arrive<2, 288>();
        } else {
            const uint32_t sel = __shfl_sync(0xffffffffu, (r & 1) ? 0x1054 : 0x5410, lane);
            mbar_wait_remote(bars + 8 * BAR_O);
            if (w == 7) TS(12);
#pragma unroll
            for (int i = 0; i < 8; i++) ob[i] = *reinterpret_cast<const uint4*>(op + i * 128);
            float d[2][4], first;
#pragma unroll
            for (int i = 0; i < 4; i++) d[0][i] = d[1][i] = 0.f;
#pragma unroll
            for (int k = 0; k < 4; k++) {
                mbar_wait(wbar + k * 8);
                if (w == 7 && k == 3) TS(14);
                uint32_t a[4][4];
#pragma unroll
                for (int i = 0; i < 4; i++) ldsm4t(a[i], wa + k * UNIT + i * 2048);
                if (k == 3) {
                    bar_sync<2, 288>();
                    first = *part;
                }
#pragma unroll
                for (int i = 0; i < 4; i++) {
                    const uint4& o = ob[(k & 1) * 4 + i];
                    mma16816(d[i & 1], a[i], k < 2 ? o.x : o.z, k < 2 ? o.y : o.w);
                }
            }
            const float v = (c & 1) ? (d[0][2] + first) + d[1][2] : (d[0][0] + first) + d[1][0];
            if (c < 2)
                asm volatile("{\n.reg .b32 t;\nprmt.b32 t, %1, 0x8000, %2;\nred.relaxed.gpu.global.add.noftz.bf16x2 [%0], t;\n}"
                         :: "l"(outp), "r"(pack_bf16(v, v)), "r"(sel) : "memory");
        }
    } else if (warp < 8 + NCW) {
        if (tid == 256 && b == 0) asm volatile("cp.async.bulk.prefetch.L2.global [%0], 1024;" :: "l"(x) : "memory");
        __syncwarp();
        cluster_sync_relaxed();
        unsigned char* flag = acc + (32 + j) * ACC_STRIDE;
        if (g == 0 && w == 0) {
            asm volatile("st.global.u32 [%0], %1;" :: "l"(out + j * 64 + lane * 2), "r"(0u) : "memory");
            __syncwarp();
            if (lane < 8) {
                asm volatile("fence.acq_rel.gpu;" ::: "memory");
                asm volatile("st.relaxed.gpu.global.u32 [%0], %1;" :: "l"(flag + lane * 4), "r"(1u) : "memory");
            }
        }
        bar_sync<3, NPAIR>();
        if (w == 0) {
            if (lane == 0) {
                unsigned f, n = 0;
                do {
                    ++n;
                    asm volatile("atom.acquire.gpu.global.or.b32 %0, [%1], 0;" : "=r"(f) : "l"(flag) : "memory");
                } while (f == 0 && n < SPIN_LIMIT);
                asm volatile("red.relaxed.gpu.global.inc.u32 [%0], 8;" :: "l"(flag) : "memory");
            }
            bar_arrive<2, 288>();
        }
        mbar_wait_remote(bars + 8 * BAR_ST);
        float wt[8];
        {
            float2 st[8];
            float M = -INFINITY, L = 0.f;
#pragma unroll
            for (int k = 0; k < 8; k++) {
                st[k] = *reinterpret_cast<const float2*>(smem + SM_ST + k * 32 + c * 8);
                M = fmaxf(M, st[k].x);
            }
#pragma unroll
            for (int k = 0; k < 8; k++) { wt[k] = ex2((st[k].x - M) * SCL); L = fmaf(wt[k], st[k].y, L); }
            const float inv = __fdividef(1.f, L);
#pragma unroll
            for (int k = 0; k < 8; k++) wt[k] *= inv;
        }
        constexpr int ND = 8 / NCW;
        uint32_t odst[ND], obar[ND];
#pragma unroll
        for (int i = 0; i < ND; i++) {
            odst[i] = mapa(sb + SM_O + j * 128 + (c >> 1) * 64 + mi * 16 + (c & 1) * 8 + (r & 1) * 4, w * ND + i);
            obar[i] = mapa(bars + 8 * BAR_O, w * ND + i);
            pin(odst[i]); pin(obar[i]);
        }
        mbar_wait_remote(bars + 8 * BAR_OP);
        if (w == 0) TS(10);
        float o[2];
#pragma unroll
        for (int i = 0; i < 2; i++) {
            float v[8];
#pragma unroll
            for (int k = 0; k < 8; k++) v[k] = *reinterpret_cast<const float*>(smem + SM_OP + k * 256 + i * 128 + lane * 4);
            o[i] = (fmaf(wt[0], v[0], wt[1] * v[1]) + fmaf(wt[2], v[2], wt[3] * v[3]))
                 + (fmaf(wt[4], v[4], wt[5] * v[5]) + fmaf(wt[6], v[6], wt[7] * v[7]));
        }
        const unsigned o2 = pack_bf16(o[0], o[1]);
#pragma unroll
        for (int i = 0; i < ND; i++) st_async32(odst[i], o2, obar[i]);
    } else {
        unsigned due = t0 + sched.first + NPF * sched.step;
        if (elect()) {
            prefetch_map(&maps.wq);
            mbar_init_tx(bars + 8 * BAR_WQ, 8 * UNIT + 1024);
            mbar_init_fence();
        }
        __syncwarp();
        asm volatile("barrier.cluster.arrive.relaxed.aligned;" ::: "memory");
        TS(35);
        if (elect()) {
#pragma unroll 1
            for (int s = 0; s < 8 - NPF; s++) {
                wait_until(due);
                tma_load(sb + (16 + s) * UNIT, &maps.wq, s * 64, b, bars + 8 * BAR_WQ);
                due += sched.step;
            }
        }
        __syncwarp();
        asm volatile("barrier.cluster.wait.aligned;" ::: "memory");
        TS(36);
        if (elect()) {
            const unsigned char* kp = kwin + (g * (unsigned)(SK * 256) + j * 131072u);
#pragma unroll 1
            for (int s = 0; s < 16; s++) {
                wait_until(due);
                bulk_load(sb + s * UNIT, kp + s * UNIT, UNIT, bars + 8 * (BAR_K + (s >> 2)));
                due += sched.step;
                if (s < NPF) tma_load(sb + (24 - NPF + s) * UNIT, &maps.wq, (8 - NPF + s) * 64, b, bars + 8 * BAR_WQ);
                if (s == NPF) bulk_load(sb + SM_X, x, 1024, bars + 8 * BAR_WQ);
                if (s == 8) { prefetch_map(&maps.v); prefetch_map(&maps.wo); }
            }
            const int key0 = g * SK + (SK - WIN) + j * 512;
#pragma unroll 1
            for (int s = 0; s < 16; s++) {
                if ((s & 7) == 0) mbar_wait(bars + 8 * (BAR_FREE + (s >> 3)));
                wait_until(due);
                tma_load(sb + (s < 8 ? 16 + s : s - 8) * UNIT, &maps.v, key0 + s * 32, 0, bars + 8 * (BAR_V + (s >> 1)));
                due += sched.step;
            }
            TS(37);
            due += sched.wo_gap;
            mbar_wait(bars + 8 * (BAR_FREE + 2));
#pragma unroll 1
            for (int s = 0; s < 8; s++) {
                wait_until(due);
                tma_load(sb + (8 + s) * UNIT, &maps.wo, g * 512 + s * 64, j, bars + 8 * (BAR_WO + s));
                due += sched.wo_step;
            }
            TS(38);
        }
    }
}

}

typedef CUresult (*EncodeFn)(CUtensorMap*, CUtensorMapDataType, cuuint32_t, void*, const cuuint64_t*, const cuuint64_t*,
                             const cuuint32_t*, const cuuint32_t*, CUtensorMapInterleave, CUtensorMapSwizzle,
                             CUtensorMapL2promotion, CUtensorMapFloatOOBfill);

static void make_map(EncodeFn enc, CUtensorMap* m, void* p, uint64_t rows, uint64_t nblk, uint32_t box_rows, uint32_t box_blks) {
    const cuuint64_t dims[3] = {64, rows, nblk}, strides[2] = {nblk * 128, 128};
    const cuuint32_t box[3] = {64, box_rows, box_blks}, es[3] = {1, 1, 1};
    enc(m, CU_TENSOR_MAP_DATA_TYPE_BFLOAT16, 3, p, dims, strides, box, es, CU_TENSOR_MAP_INTERLEAVE_NONE,
        CU_TENSOR_MAP_SWIZZLE_128B, CU_TENSOR_MAP_L2_PROMOTION_NONE, CU_TENSOR_MAP_FLOAT_OOB_FILL_NONE);
}

extern "C" void kernel_launch(void* const* d_in, const int* in_sizes, int n_in, void* d_out, int out_size) {
    EncodeFn enc = nullptr;
    cudaDriverEntryPointQueryResult qr;
    cudaGetDriverEntryPoint("cuTensorMapEncodeTiled", (void**)&enc, cudaEnableDefault, &qr);
    Maps maps;
    make_map(enc, &maps.wq, d_in[3], 512, 64, 64, 1);
    make_map(enc, &maps.v, d_in[2], 8 * SK, 2, 32, 2);
    make_map(enc, &maps.wo, d_in[4], 4096, 8, 64, 1);
    void* acc = nullptr;
    cudaGetSymbolAddress(&acc, g_scratch);
    cudaFuncSetAttribute(decode_fused_kernel, cudaFuncAttributeMaxDynamicSharedMemorySize, SMEM_BYTES);
    Sched s = {-700, 167, 150, 172};
    decode_fused_kernel<<<NCTA, NTHREADS, SMEM_BYTES>>>((const unsigned char*)d_in[3] + (8 - NPF) * 64 * 8192, s,
                                                        (const unsigned char*)d_in[1] + (size_t)(SK - WIN) * 256,
                                                        (const unsigned char*)d_in[0], (unsigned short*)d_out,
                                                        (unsigned char*)acc, maps);
}
```

```cpp
#include <cuda_runtime.h>
#include <cuda.h>
#include <cuda_bf16.h>
#include <stdint.h>

namespace {

constexpr int SK = 32768, WIN = 4096;
constexpr int NCTA = 64, CLUSTER = 8;
constexpr int NTHREADS = 320;

constexpr int BAR_V = 0;
constexpr int BAR_WO = 8;
constexpr int BAR_Q = 16, BAR_ST = 17, BAR_OP = 18, BAR_O = 19;
constexpr int BAR_K = 20;
constexpr int BAR_FREE = 24;
constexpr int BAR_WQ = 27;

constexpr int UNIT = 8192;
constexpr int SM_OP = 24 * UNIT;
constexpr int SM_RED = SM_OP + 2048;
constexpr int SM_Q = SM_RED + 2048;
constexpr int Q_ROW = 320;
constexpr int SM_P = SM_Q + 4 * Q_ROW;
constexpr int P_ROW = 1088;
constexpr int SM_MAX = SM_P + 4 * P_ROW;
constexpr int SM_SUM = SM_MAX + 128;
constexpr int SM_ST = SM_SUM + 128;
constexpr int SM_O = SM_ST + 256;
constexpr int SM_X = SM_O + 1024;
constexpr int SM_BAR = SM_X + 1024;
constexpr int SMEM_BYTES = SM_BAR + 256;

constexpr int NPF = 2;
constexpr unsigned SPIN_LIMIT = 1u << 20;

constexpr int FLAG_STRIDE = 256;
__device__ __align__(256) unsigned char g_scratch[CLUSTER * FLAG_STRIDE];

struct Sched { int first, step, wo_gap, wo_step; };
struct Maps { CUtensorMap wq, v, wo; };

__device__ __forceinline__ unsigned now_ns() { unsigned t; asm volatile("mov.u32 %0, %%globaltimer_lo;" : "=r"(t)); return t; }
__device__ __forceinline__ void wait_until(unsigned t) {
    unsigned n = 0;
    do { ++n; } while ((int)(now_ns() - t) < 0 && n < 4096);
}
__device__ __forceinline__ uint32_t smem_u32(const void* p) { return (uint32_t)__cvta_generic_to_shared(p); }
__device__ __forceinline__ bool elect() {
    unsigned p; asm volatile("{\n.reg .pred p;\nelect.sync _|p, 0xffffffff;\nselp.u32 %0, 1, 0, p;\n}" : "=r"(p)); return p;
}
__device__ __forceinline__ void mbar_init(uint32_t bar, uint32_t cnt) {
    asm volatile("mbarrier.init.shared::cta.b64 [%0], %1;" :: "r"(bar), "r"(cnt) : "memory");
}
__device__ __forceinline__ void mbar_init_tx(uint32_t bar, uint32_t bytes) {
    mbar_init(bar, 1);
    asm volatile("mbarrier.arrive.expect_tx.shared::cta.b64 _, [%0], %1;" :: "r"(bar), "r"(bytes) : "memory");
}
__device__ __forceinline__ void mbar_init_fence() { asm volatile("fence.mbarrier_init.release.cluster;" ::: "memory"); }
__device__ __forceinline__ void mbar_arrive(uint32_t bar) {
    asm volatile("mbarrier.arrive.shared::cta.b64 _, [%0];" :: "r"(bar) : "memory");
}
__device__ __forceinline__ void mbar_wait(uint32_t bar) {
    unsigned ok, n = 0;
    do {
        ++n;
        asm volatile("{\n.reg .pred p;\nmbarrier.try_wait.parity.shared::cta.b64 p, [%1], 0;\nselp.u32 %0, 1, 0, p;\n}"
                     : "=r"(ok) : "r"(bar) : "memory");
    } while (!ok && n < SPIN_LIMIT);
}
__device__ __forceinline__ void mbar_wait_remote(uint32_t bar) {
    unsigned ok, n = 0;
    do {
        ++n;
        asm volatile("{\n.reg .pred p;\nmbarrier.try_wait.parity.relaxed.cluster.shared::cta.b64 p, [%1], 0;\nselp.u32 %0, 1, 0, p;\n}"
                     : "=r"(ok) : "r"(bar) : "memory");
    } while (!ok && n < SPIN_LIMIT);
    asm volatile("fence.acquire.sync_restrict::shared::cluster.cluster;" ::: "memory");
}
__device__ __forceinline__ void bulk_load(uint32_t dst, const void* src, uint32_t bytes, uint32_t bar) {
    asm volatile("cp.async.bulk.shared::cluster.global.mbarrier::complete_tx::bytes [%0], [%1], %2, [%3];"
                 :: "r"(dst), "l"(src), "r"(bytes), "r"(bar) : "memory");
}
__device__ __forceinline__ void tma_load(uint32_t dst, const CUtensorMap* m, int row, int blk, uint32_t bar) {
    asm volatile("cp.async.bulk.tensor.3d.shared::cluster.global.mbarrier::complete_tx::bytes [%0], [%1, {%2, %3, %4}], [%5];"
                 :: "r"(dst), "l"(m), "r"(0), "r"(row), "r"(blk), "r"(bar) : "memory");
}
__device__ __forceinline__ void prefetch_map(const CUtensorMap* m) {
    asm volatile("prefetch.tensormap [%0];" :: "l"(m) : "memory");
}
__device__ __forceinline__ uint32_t mapa(uint32_t addr, uint32_t rank) {
    uint32_t r; asm("mapa.shared::cluster.u32 %0, %1, %2;" : "=r"(r) : "r"(addr), "r"(rank)); return r;
}
__device__ __forceinline__ void st_async32(uint32_t dst, unsigned v, uint32_t bar) {
    asm volatile("st.async.shared::cluster.mbarrier::complete_tx::bytes.b32 [%0], %1, [%2];" :: "r"(dst), "r"(v), "r"(bar) : "memory");
}
__device__ __forceinline__ void st_async64(uint32_t dst, float a, float b, uint32_t bar) {
    asm volatile("st.async.shared::cluster.mbarrier::complete_tx::bytes.v2.f32 [%0], {%1,%2}, [%3];"
                 :: "r"(dst), "f"(a), "f"(b), "r"(bar) : "memory");
}
template <int ID, int N> __device__ __forceinline__ void bar_sync() { asm volatile("bar.sync %0, %1;" :: "n"(ID), "n"(N) : "memory"); }
template <int ID, int N> __device__ __forceinline__ void bar_arrive() { asm volatile("bar.arrive %0, %1;" :: "n"(ID), "n"(N) : "memory"); }
__device__ __forceinline__ void cluster_sync_relaxed() {
    asm volatile("barrier.cluster.arrive.relaxed.aligned;\nbarrier.cluster.wait.aligned;" ::: "memory");
}
__device__ __forceinline__ void ldsm4t(uint32_t (&r)[4], uint32_t addr) {
    asm volatile("ldmatrix.sync.aligned.m8n8.x4.trans.shared.b16 {%0,%1,%2,%3}, [%4];"
                 : "=r"(r[0]), "=r"(r[1]), "=r"(r[2]), "=r"(r[3]) : "r"(addr) : "memory");
}
__device__ __forceinline__ void mma16816(float (&d)[4], uint32_t a0, uint32_t a1, uint32_t a2, uint32_t a3, uint32_t b0, uint32_t b1) {
    asm volatile("mma.sync.aligned.m16n8k16.row.col.f32.bf16.bf16.f32 {%0,%1,%2,%3}, {%4,%5,%6,%7}, {%8,%9}, {%0,%1,%2,%3};"
                 : "+f"(d[0]), "+f"(d[1]), "+f"(d[2]), "+f"(d[3])
                 : "r"(a0), "r"(a1), "r"(a2), "r"(a3), "r"(b0), "r"(b1));
}
__device__ __forceinline__ void mma16816(float (&d)[4], const uint32_t (&a)[4], uint32_t b0, uint32_t b1) {
    mma16816(d, a[0], a[1], a[2], a[3], b0, b1);
}
__device__ __forceinline__ float bf_lo(unsigned u) { return __uint_as_float(u << 16); }
__device__ __forceinline__ float bf_hi(unsigned u) { return __uint_as_float(u & 0xffff0000u); }
__device__ __forceinline__ unsigned pack_bf16(float lo, float hi) {
    unsigned r; asm("cvt.rn.bf16x2.f32 %0, %1, %2;" : "=r"(r) : "f"(hi), "f"(lo)); return r;
}
__device__ __forceinline__ float ex2(float x) { float y; asm("ex2.approx.ftz.f32 %0, %1;" : "=f"(y) : "f"(x)); return y; }
template <typename T> __device__ __forceinline__ void pin(T*& p) { asm volatile("" : "+l"(p)); }
__device__ __forceinline__ void pin(uint32_t& v) { asm volatile("" : "+r"(v)); }

constexpr float SCALE = 0.08838834764831845f;
constexpr float LOG2E = 1.4426950408889634f;

__global__ void __cluster_dims__(CLUSTER, 1, 1) __launch_bounds__(NTHREADS, 1)
decode_fused_kernel(const unsigned char* __restrict__ wq_tail, const Sched sched, const unsigned char* __restrict__ kwin,
                    const unsigned char* __restrict__ x, unsigned short* __restrict__ out, unsigned char* __restrict__ flags,
                    const __grid_constant__ Maps maps) {
    extern __shared__ __align__(1024) unsigned char smem[];
    const int tid = threadIdx.x;
    const unsigned b = blockIdx.x, g = b >> 3, j = b & 7;
    asm volatile("{\n.reg .pred p;\nsetp.eq.u32 p, %1, 64;\n@p cp.async.bulk.prefetch.L2.global [%0], %2;\n}"
                 :: "l"(wq_tail + (size_t)b * (NPF * UNIT)), "r"(tid), "n"(NPF * UNIT) : "memory");
    const unsigned t0 = now_ns();
    const uint32_t sb = smem_u32(smem);
    const uint32_t bars = sb + SM_BAR;
    const int warp = __shfl_sync(0xffffffffu, tid >> 5, 0);
    const int lane = tid & 31, w = warp & 7;
    const int r = lane >> 2, c = lane & 3, mi = lane >> 3, li = lane & 7;
    if (warp < 8) {
        if (elect()) {
            mbar_init_tx(bars + 8 * (BAR_V + w), 2 * UNIT);
            mbar_init_tx(bars + 8 * (BAR_WO + w), UNIT);
            mbar_init_tx(bars + 8 * (BAR_Q + w), w >= 4 ? 4 * UNIT : w == 1 ? 256 : w == 2 ? 2048 : 1024);
            if (w < 3) mbar_init(bars + 8 * (BAR_FREE + w), 8);
            mbar_init_fence();
        }
        __syncwarp();
        cluster_sync_relaxed();
        {
            const uint32_t qa = sb + (16 + w) * UNIT + ((mi >> 1) * 8 + li) * 128;
            float d[4][4];
#pragma unroll
            for (int t = 0; t < 4; t++)
#pragma unroll
                for (int i = 0; i < 4; i++) d[t][i] = 0.f;
            mbar_wait(bars + 8 * BAR_WQ);
#pragma unroll 1
            for (int ks = 0; ks < 4; ks++) {
                const unsigned char* xp = smem + SM_X + w * 128 + ks * 32 + c * 4;
                const uint32_t x0 = *reinterpret_cast<const uint32_t*>(xp), x1 = *reinterpret_cast<const uint32_t*>(xp + 16);
#pragma unroll
                for (int t = 0; t < 4; t++) {
                    uint32_t a[4];
                    ldsm4t(a, qa + ks * 2048 + (((t * 2 + (mi & 1)) ^ li) * 16));
                    mma16816(d[t], a, x0, x1);
                }
            }
            __syncwarp();
            if (lane == 0) mbar_arrive(bars + 8 * BAR_FREE);
            float* rp = reinterpret_cast<float*>(smem + SM_RED) + w * 64 + c * 16 + r;
            rp[0] = (c & 2) ? ((c & 1) ? d[3][0] : d[2][0]) : ((c & 1) ? d[1][0] : d[0][0]);
            rp[8] = (c & 2) ? ((c & 1) ? d[3][2] : d[2][2]) : ((c & 1) ? d[1][2] : d[0][2]);
        }
        __syncwarp();
        bar_sync<1, 256>();
        {
            float s0 = 0.f, s1 = 0.f;
#pragma unroll
            for (int k = 0; k < 8; k++) {
                const float2 v = *reinterpret_cast<const float2*>(smem + SM_RED + k * 256 + lane * 8);
                s0 += v.x; s1 += v.y;
            }
            st_async32(mapa(sb + SM_Q + (j >> 1) * Q_ROW + (j & 1) * 128 + lane * 4, w), pack_bf16(s0, s1),
                       mapa(bars + 8 * BAR_Q, w));
        }
        mbar_wait_remote(bars + 8 * BAR_Q);
        const int ts = c >> 1, h0 = (c & 1) * 2, i0 = (r ^ ts) & 1;
        float s[2][4];
        {
            uint4 qb[4];
#pragma unroll
            for (int t = 0; t < 4; t++)
                qb[t] = *reinterpret_cast<const uint4*>(smem + SM_Q + (r & 3) * Q_ROW + (((t * 4 + c) ^ (r & 4)) * 16));
#pragma unroll
            for (int k = 0; k < 4; k++) s[0][k] = s[1][k] = 0.f;
#pragma unroll 1
            for (int i = 0; i < 4; i++) {
                const unsigned char* ka = smem + i * 4 * UNIT + (w * 16 + r) * 256 + c * 16;
                const int sw = ((r ^ i) & 1) * 64;
                mbar_wait(bars + 8 * (BAR_K + i));
                uint4 lo[4], hi[4];
#pragma unroll
                for (int t = 0; t < 4; t++) {
                    lo[t] = *reinterpret_cast<const uint4*>(ka + ((t * 64) ^ sw));
                    hi[t] = *reinterpret_cast<const uint4*>(ka + ((t * 64) ^ sw) + 2048);
                }
                float s1[4], s2[4];
#pragma unroll
                for (int k = 0; k < 4; k++) s1[k] = s2[k] = 0.f;
#pragma unroll
                for (int t = 0; t < 4; t++) {
                    mma16816(s1, lo[t].x, hi[t].x, lo[t].y, hi[t].y, qb[t].x, qb[t].y);
                    mma16816(s2, lo[t].z, hi[t].z, lo[t].w, hi[t].w, qb[t].z, qb[t].w);
                }
#pragma unroll
                for (int k = 0; k < 4; k++) {
                    const float v = s1[k] + s2[k];
                    s[0][k] = (i == i0) ? v : s[0][k];
                    s[1][k] = (i == i0 + 2) ? v : s[1][k];
                }
                __syncwarp();
                if ((i & 1) && lane == 0) mbar_arrive(bars + 8 * (BAR_FREE + 1 + (i >> 1)));
            }
        }
#pragma unroll
        for (int u = 0; u < 2; u++)
#pragma unroll
            for (int k = 0; k < 4; k += 2) {
                const unsigned t = pack_bf16(s[u][k], s[u][k + 1]);
                const unsigned t2 = pack_bf16(bf_lo(t) * SCALE, bf_hi(t) * SCALE);
                s[u][k] = bf_lo(t2); s[u][k + 1] = bf_hi(t2);
            }
        {
            float m0 = fmaxf(fmaxf(s[0][0], s[0][2]), fmaxf(s[1][0], s[1][2]));
            float m1 = fmaxf(fmaxf(s[0][1], s[0][3]), fmaxf(s[1][1], s[1][3]));
#pragma unroll
            for (int o = 2; o < 32; o <<= 1) {
                m0 = fmaxf(m0, __shfl_xor_sync(0xffffffffu, m0, o));
                m1 = fmaxf(m1, __shfl_xor_sync(0xffffffffu, m1, o));
            }
            if (lane < 2) *reinterpret_cast<float2*>(smem + SM_MAX + w * 16 + lane * 8) = make_float2(m0, m1);
        }
        __syncwarp();
        bar_sync<1, 256>();
        {
            float m0 = -INFINITY, m1 = -INFINITY;
#pragma unroll
            for (int k = 0; k < 8; k++) {
                const float2 m = *reinterpret_cast<const float2*>(smem + SM_MAX + k * 16 + (c & 1) * 8);
                m0 = fmaxf(m0, m.x); m1 = fmaxf(m1, m.y);
            }
            float l0 = 0.f, l1 = 0.f;
#pragma unroll
            for (int u = 0; u < 2; u++) {
                const unsigned p01 = pack_bf16(ex2((s[u][0] - m0) * LOG2E), ex2((s[u][1] - m1) * LOG2E));
                const unsigned p23 = pack_bf16(ex2((s[u][2] - m0) * LOG2E), ex2((s[u][3] - m1) * LOG2E));
                unsigned char* pp = smem + SM_P + h0 * P_ROW + ((2 * u + i0) * 4 + (w >> 1)) * 64 + (r >> 1) * 16 + (w & 1) * 8 + (r & 1) * 2;
                *reinterpret_cast<unsigned short*>(pp) = (unsigned short)p01;
                *reinterpret_cast<unsigned short*>(pp + P_ROW) = (unsigned short)(p01 >> 16);
                *reinterpret_cast<unsigned short*>(pp + 4) = (unsigned short)p23;
                *reinterpret_cast<unsigned short*>(pp + P_ROW + 4) = (unsigned short)(p23 >> 16);
                l0 += bf_lo(p01) + bf_lo(p23); l1 += bf_hi(p01) + bf_hi(p23);
            }
#pragma unroll
            for (int o = 2; o < 32; o <<= 1) {
                l0 += __shfl_xor_sync(0xffffffffu, l0, o);
                l1 += __shfl_xor_sync(0xffffffffu, l1, o);
            }
            if (lane < 2) *reinterpret_cast<float2*>(smem + SM_SUM + w * 16 + lane * 8) = make_float2(l0, l1);
        }
        __syncwarp();
        bar_sync<1, 256>();
        if (lane < 4) {
            float m = -INFINITY, l = 0.f;
#pragma unroll
            for (int k = 0; k < 8; k++) {
                m = fmaxf(m, *reinterpret_cast<const float*>(smem + SM_MAX + k * 16 + lane * 4));
                l += *reinterpret_cast<const float*>(smem + SM_SUM + k * 16 + lane * 4);
            }
            st_async64(mapa(sb + SM_ST + j * 32 + lane * 8, w), m, l, mapa(bars + 8 * BAR_ST, w));
        }
        __syncwarp();
        bar_arrive<3, 288>();
        const uint32_t ta = sb + ((mi >> 1) * 8 + li) * 128 + ((((w & 3) * 2 + (mi & 1)) ^ li) * 16);
        {
            float oa[4][4];
#pragma unroll
            for (int i = 0; i < 4; i++) oa[0][i] = oa[1][i] = oa[2][i] = oa[3][i] = 0.f;
            const unsigned char* pp = smem + SM_P + (r & 3) * P_ROW + c * 16;
            uint32_t odst = mapa(sb + SM_OP + j * 256 + ((r & 1) * 32 + (r >> 1) * 8 + ts * 4 + h0) * 4, w);
            uint32_t obar = mapa(bars + 8 * BAR_OP, w);
            pin(odst); pin(obar);
#pragma unroll 1
            for (int u = 0; u < 8; u++) {
                const uint4 p0 = *reinterpret_cast<const uint4*>(pp + u * 128);
                const uint4 p1 = *reinterpret_cast<const uint4*>(pp + u * 128 + 64);
                const uint32_t va = ta + (w >> 2) * 4096 + (u < 4 ? 16 + 2 * u : 2 * u - 8) * UNIT;
                mbar_wait(bars + 8 * (BAR_V + u));
                uint32_t a[4][4];
                ldsm4t(a[0], va);
                ldsm4t(a[1], va + 2048);
                ldsm4t(a[2], va + UNIT);
                ldsm4t(a[3], va + UNIT + 2048);
                mma16816(oa[0], a[0], p0.x, p0.y);
                mma16816(oa[1], a[1], p0.z, p0.w);
                mma16816(oa[2], a[2], p1.x, p1.y);
                mma16816(oa[3], a[3], p1.z, p1.w);
            }
            float v[4];
#pragma unroll
            for (int i = 0; i < 4; i++) v[i] = (oa[0][i] + oa[1][i]) + (oa[2][i] + oa[3][i]);
            st_async64(odst, ts ? v[2] : v[0], ts ? v[3] : v[1], obar);
        }
        const unsigned col = j * 64 + (w & 3) * 16 + (c & 1) * 8 + r;
        unsigned short* outp = out + (col & ~1u);
        pin(outp);
        float* part = reinterpret_cast<float*>(smem + SM_RED) + (col & 63);
        const uint32_t wa = ta + (8 + (w & 4)) * UNIT, wbar = bars + 8 * (BAR_WO + (w & 4));
        const unsigned char* op = smem + SM_O + (w & 4) * 16 + c * 16;
        uint4 ob[8];
        if (w < 4) {
            uint32_t a[16][4];
#pragma unroll
            for (int k = 0; k < 4; k++) {
                mbar_wait(wbar + k * 8);
#pragma unroll
                for (int i = 0; i < 4; i++) ldsm4t(a[4 * k + i], wa + k * UNIT + i * 2048);
            }
            mbar_wait_remote(bars + 8 * BAR_O);
#pragma unroll
            for (int i = 0; i < 8; i++) ob[i] = *reinterpret_cast<const uint4*>(op + i * 128);
            float d[4][4];
#pragma unroll
            for (int i = 0; i < 4; i++) d[0][i] = d[1][i] = d[2][i] = d[3][i] = 0.f;
#pragma unroll
            for (int i = 0; i < 8; i++) {
                mma16816(d[(i & 1) * 2], a[i], ob[i].x, ob[i].y);
                mma16816(d[(i & 1) * 2 + 1], a[8 + i], ob[i].z, ob[i].w);
            }
            if (c < 2) *part = c ? (d[0][2] + d[1][2]) + (d[2][2] + d[3][2]) : (d[0][0] + d[1][0]) + (d[2][0] + d[3][0]);
            __syncwarp();
            bar_arrive<2, 288>();
        } else {
            const uint32_t sel = __shfl_sync(0xffffffffu, (r & 1) ? 0x1054 : 0x5410, lane);
            mbar_wait_remote(bars + 8 * BAR_O);
#pragma unroll
            for (int i = 0; i < 8; i++) ob[i] = *reinterpret_cast<const uint4*>(op + i * 128);
            float d[2][4], first;
#pragma unroll
            for (int i = 0; i < 4; i++) d[0][i] = d[1][i] = 0.f;
#pragma unroll
            for (int k = 0; k < 4; k++) {
                mbar_wait(wbar + k * 8);
                uint32_t a[4][4];
#pragma unroll
                for (int i = 0; i < 4; i++) ldsm4t(a[i], wa + k * UNIT + i * 2048);
                if (k == 3) {
                    bar_sync<2, 288>();
                    first = *part;
                }
#pragma unroll
                for (int i = 0; i < 4; i++) {
                    const uint4& o = ob[(k & 1) * 4 + i];
                    mma16816(d[i & 1], a[i], k < 2 ? o.x : o.z, k < 2 ? o.y : o.w);
                }
            }
            const float v = (c & 1) ? (d[0][2] + first) + d[1][2] : (d[0][0] + first) + d[1][0];
            if (c < 2)
                asm volatile("{\n.reg .b32 t;\nprmt.b32 t, %1, 0x8000, %2;\nred.relaxed.gpu.global.add.noftz.bf16x2 [%0], t;\n}"
                             :: "l"(outp), "r"(pack_bf16(v, v)), "r"(sel) : "memory");
        }
    } else if (warp == 8) {
        if (tid == 256 && b == 0) asm volatile("cp.async.bulk.prefetch.L2.global [%0], 1024;" :: "l"(x) : "memory");
        __syncwarp();
        cluster_sync_relaxed();
        unsigned char* flag = flags + j * FLAG_STRIDE;
        if (g == 0) {
            asm volatile("st.global.u32 [%0], %1;" :: "l"(out + j * 64 + lane * 2), "r"(0u) : "memory");
            __syncwarp();
            if (lane < 8) {
                asm volatile("fence.acq_rel.gpu;" ::: "memory");
                asm volatile("st.relaxed.gpu.global.u32 [%0], %1;" :: "l"(flag + lane * 4), "r"(1u) : "memory");
            }
            __syncwarp();
        }
        bar_sync<3, 288>();
        if (lane == 0) {
            unsigned f, n = 0;
            do {
                ++n;
                asm volatile("atom.acquire.gpu.global.exch.b32 %0, [%1], 0;" : "=r"(f) : "l"(flag + g * 4) : "memory");
            } while (f == 0 && n < SPIN_LIMIT);
        }
        __syncwarp();
        bar_arrive<2, 288>();
        mbar_wait_remote(bars + 8 * BAR_ST);
        float wt[8];
        {
            float2 st[8];
            float M = -INFINITY, L = 0.f;
#pragma unroll
            for (int k = 0; k < 8; k++) {
                st[k] = *reinterpret_cast<const float2*>(smem + SM_ST + k * 32 + c * 8);
                M = fmaxf(M, st[k].x);
            }
#pragma unroll
            for (int k = 0; k < 8; k++) { wt[k] = ex2((st[k].x - M) * LOG2E); L = fmaf(wt[k], st[k].y, L); }
            const float inv = __fdividef(1.f, L);
#pragma unroll
            for (int k = 0; k < 8; k++) wt[k] *= inv;
        }
        uint32_t odst[8], obar[8];
#pragma unroll
        for (int i = 0; i < 8; i++) {
            odst[i] = mapa(sb + SM_O + j * 128 + (c >> 1) * 64 + mi * 16 + (c & 1) * 8 + (r & 1) * 4, i);
            obar[i] = mapa(bars + 8 * BAR_O, i);
            pin(odst[i]); pin(obar[i]);
        }
        mbar_wait_remote(bars + 8 * BAR_OP);
        float o[2];
#pragma unroll
        for (int i = 0; i < 2; i++) {
            float v[8];
#pragma unroll
            for (int k = 0; k < 8; k++) v[k] = *reinterpret_cast<const float*>(smem + SM_OP + k * 256 + i * 128 + lane * 4);
            o[i] = (fmaf(wt[0], v[0], wt[1] * v[1]) + fmaf(wt[2], v[2], wt[3] * v[3]))
                 + (fmaf(wt[4], v[4], wt[5] * v[5]) + fmaf(wt[6], v[6], wt[7] * v[7]));
        }
        const unsigned o2 = pack_bf16(o[0], o[1]);
#pragma unroll
        for (int i = 0; i < 8; i++) st_async32(odst[i], o2, obar[i]);
    } else {
        unsigned due = t0 + sched.first + NPF * sched.step + g * 16;
        if (elect()) {
            prefetch_map(&maps.wq);
            mbar_init_tx(bars + 8 * BAR_WQ, 8 * UNIT + 1024);
            mbar_init_fence();
        }
        __syncwarp();
        asm volatile("barrier.cluster.arrive.relaxed.aligned;" ::: "memory");
        if (elect()) {
#pragma unroll 1
            for (int s = 0; s < 8 - NPF; s++) {
                wait_until(due);
                tma_load(sb + (16 + s) * UNIT, &maps.wq, s * 64, b, bars + 8 * BAR_WQ);
                due += sched.step;
            }
        }
        __syncwarp();
        asm volatile("barrier.cluster.wait.aligned;" ::: "memory");
        if (elect()) {
            const unsigned char* kp = kwin + (g * (unsigned)(SK * 256) + j * 131072u);
#pragma unroll 1
            for (int s = 0; s < 16; s++) {
                wait_until(due);
                bulk_load(sb + s * UNIT, kp + s * UNIT, UNIT, bars + 8 * (BAR_K + (s >> 2)));
                due += sched.step;
                if (s < NPF) tma_load(sb + (24 - NPF + s) * UNIT, &maps.wq, (8 - NPF + s) * 64, b, bars + 8 * BAR_WQ);
                if (s == NPF) bulk_load(sb + SM_X, x, 1024, bars + 8 * BAR_WQ);
                if (s == 8) { prefetch_map(&maps.v); prefetch_map(&maps.wo); }
            }
            const int key0 = g * SK + (SK - WIN) + j * 512;
#pragma unroll 1
            for (int s = 0; s < 16; s++) {
                if ((s & 7) == 0) mbar_wait(bars + 8 * (BAR_FREE + (s >> 3)));
                wait_until(due);
                tma_load(sb + (s < 8 ? 16 + s : s - 8) * UNIT, &maps.v, key0 + s * 32, 0, bars + 8 * (BAR_V + (s >> 1)));
                due += sched.step;
            }
            due += sched.wo_gap;
            mbar_wait(bars + 8 * (BAR_FREE + 2));
#pragma unroll 1
            for (int s = 0; s < 8; s++) {
                wait_until(due);
                tma_load(sb + (8 + s) * UNIT, &maps.wo, g * 512 + s * 64, j, bars + 8 * (BAR_WO + s));
                due += sched.wo_step;
            }
        }
    }
}

}

typedef CUresult (*EncodeFn)(CUtensorMap*, CUtensorMapDataType, cuuint32_t, void*, const cuuint64_t*, const cuuint64_t*,
                             const cuuint32_t*, const cuuint32_t*, CUtensorMapInterleave, CUtensorMapSwizzle,
                             CUtensorMapL2promotion, CUtensorMapFloatOOBfill);

static void make_map(EncodeFn enc, CUtensorMap* m, void* p, uint64_t rows, uint64_t nblk, uint32_t box_rows, uint32_t box_blks) {
    const cuuint64_t dims[3] = {64, rows, nblk}, strides[2] = {nblk * 128, 128};
    const cuuint32_t box[3] = {64, box_rows, box_blks}, es[3] = {1, 1, 1};
    enc(m, CU_TENSOR_MAP_DATA_TYPE_BFLOAT16, 3, p, dims, strides, box, es, CU_TENSOR_MAP_INTERLEAVE_NONE,
        CU_TENSOR_MAP_SWIZZLE_128B, CU_TENSOR_MAP_L2_PROMOTION_NONE, CU_TENSOR_MAP_FLOAT_OOB_FILL_NONE);
}

extern "C" void kernel_launch(void* const* d_in, const int* in_sizes, int n_in, void* d_out, int out_size) {
    EncodeFn enc = nullptr;
    cudaDriverEntryPointQueryResult qr;
    cudaGetDriverEntryPoint("cuTensorMapEncodeTiled", (void**)&enc, cudaEnableDefault, &qr);
    Maps maps;
    make_map(enc, &maps.wq, d_in[3], 512, 64, 64, 1);
    make_map(enc, &maps.v, d_in[2], 8 * SK, 2, 32, 2);
    make_map(enc, &maps.wo, d_in[4], 4096, 8, 64, 1);
    void* flags = nullptr;
    cudaGetSymbolAddress(&flags, g_scratch);
    cudaFuncSetAttribute(decode_fused_kernel, cudaFuncAttributeMaxDynamicSharedMemorySize, SMEM_BYTES);
    int dev = 0, khz = 0, bits = 0;
    cudaGetDevice(&dev);
    cudaDeviceGetAttribute(&khz, cudaDevAttrMemoryClockRate, dev);
    cudaDeviceGetAttribute(&bits, cudaDevAttrGlobalMemoryBusWidth, dev);
    const double unit_ns = khz > 0 && bits > 0 ? (double)NCTA * UNIT / (2e-6 * khz * bits / 8) : 156.4;
    Sched s = {-756, (int)(unit_ns * 1.055 + 0.5), 240, (int)(unit_ns * 1.074 + 0.5)};
    decode_fused_kernel<<<NCTA, NTHREADS, SMEM_BYTES>>>((const unsigned char*)d_in[3] + (8 - NPF) * 64 * 8192, s,
                                                        (const unsigned char*)d_in[1] + (size_t)(SK - WIN) * 256,
                                                        (const unsigned char*)d_in[0], (unsigned short*)d_out,
                                                        (unsigned char*)flags, maps);
}
```
